```python
import torch

def _softmax(x, axis=-1):
    return torch.softmax(x, dim=axis)
def _gelu(x):
    return torch.nn.functional.gelu(x, approximate="tanh")
def _silu(x):
    return torch.nn.functional.silu(x)
def _sigmoid(x):
    return torch.sigmoid(x)
def _layernorm(x, axis=-1, eps=1e-5):
    m = x.mean(dim=axis, keepdim=True)
    v = x.var(dim=axis, keepdim=True, unbiased=False)
    return (x - m) / torch.sqrt(v + eps)
def _scatter_add(tgt, idx, src, axis=0):
    return tgt.clone().index_add_(axis, idx, src)
def _segment_sum(src, seg, n):
    out = torch.zeros((n,) + src.shape[1:], dtype=src.dtype)
    return out.index_add_(0, seg, src)
def _pad(x, pw):
    flat = tuple(v for pair in reversed(pw) for v in pair)
    return torch.nn.functional.pad(x, flat)

kernel_name = 'standalone__linear_kernel_performer__prompt'

def setup_inputs():

    _w = (lambda a: (lambda t: t.to(torch.bfloat16) if t.is_floating_point() else t)(torch.as_tensor(a)))
    B, H, S, D = 1, 16, 2048, 256
    M = D
    return {
        "q": _w((lambda *s: torch.randn(*s, dtype=torch.bfloat16) * 0.05)(B, H, S, D)),
        "k": _w((lambda *s: torch.randn(*s, dtype=torch.bfloat16) * 0.4)(B, H, S, D)),
        "v": _w((lambda *s: torch.randn(*s, dtype=torch.bfloat16) * 0.4)(B, H, S, D)),
        "proj": _w((lambda *s: torch.randn(*s, dtype=torch.bfloat16) * 0.4)(M, D)),
    }

def reference(q, k, v, proj):
    B, H, S, D = q.shape
    M = proj.shape[0]
    scale = D ** -0.25
    qs = q * scale
    ks = k * scale
    qw = torch.einsum("bhsd,md->bhsm", qs, proj)
    kw = torch.einsum("bhsd,md->bhsm", ks, proj)
    qn = torch.einsum("bhsd,bhsd->bhs", qs, qs)[..., None] * 0.5
    kn = torch.einsum("bhsd,bhsd->bhs", ks, ks)[..., None] * 0.5
    inv_sqrt_m = M ** -0.5
    phi_q = torch.exp(qw - qn) * inv_sqrt_m
    phi_k = torch.exp(kw - kn) * inv_sqrt_m
    kv = torch.einsum("bhsm,bhsd->bhmd", phi_k, v)
    ksum = torch.einsum("bhsm->bhm", phi_k)
    num = torch.einsum("bhsm,bhmd->bhsd", phi_q, kv)
    den = torch.einsum("bhsm,bhm->bhs", phi_q, ksum)[..., None] + 1e-6
    return num / den
```

```cpp
#include <cuda_runtime.h>
#include <cuda_bf16.h>
#include <cuda.h>
#include <stdint.h>

namespace {

constexpr int kHeads = 16;
constexpr int kSeq = 2048;
constexpr int kDim = 256;

constexpr uint32_t SM_P0 = 0;
constexpr uint32_t SM_SLOT = 65536;
constexpr uint32_t SLOT_BYTES = 32768;
constexpr uint32_t SM_BAR = SM_SLOT + 5 * SLOT_BYTES;
constexpr uint32_t SM_NORM = SM_BAR + 512;
constexpr uint32_t SM_KS = SM_NORM + 1024;
constexpr uint32_t SM_TOTAL = SM_KS + 512;

constexpr int B_PROJ = 0;
constexpr int B_KFULL = 1;
constexpr int B_KEMPTY = 4;
constexpr int B_VFULL = 7;
constexpr int B_VEMPTY = 9;
constexpr int B_NORM = 25;
constexpr int B_ACONS = 29;
constexpr int B_PO01 = 15;
constexpr int B_PO23 = 16;
constexpr int B_ZERO = 17;
constexpr int B_DUMPED = 18;
constexpr int B_STG = 11;
constexpr int B_SFREE = 13;
constexpr int B_PDEAD = 19;
constexpr int B_KSUM = 20;
constexpr int B_KV = 21;

#define PO_DSMEM 0
#define KV_MC 0
#define FLAG_FENCE 0
#define B_PF 0
#define A0_TRIG 2
#define EARLY_PF 1
#define START_ORDER 0
#define ABL_NORED 0
#define ABL_NOOUT 0
constexpr int kSpinLimit = 1 << 21;

__device__ uint4 g_kvacc[kHeads * 8192];
__device__ float g_ksum[kHeads * 256];
__device__ unsigned g_flag_zero[kHeads * 32];
__device__ unsigned g_flag_dump[kHeads * 32];
#define PROF(i) do {} while (0)
#define PROFW(i) do {} while (0)
#define PROFA(i) do {} while (0)
#define PROFS(i) do {} while (0)
#define CLK(i) do {} while (0)
#define CLKS(i) do {} while (0)
#define CLKP(i) do {} while (0)
#define CLKALL(i) do {} while (0)
#define CLKG4(i) do {} while (0)

__device__ __forceinline__ void mbar_init(uint32_t bar, uint32_t cnt) {
    asm volatile("mbarrier.init.shared::cta.b64 [%0], %1;" :: "r"(bar), "r"(cnt) : "memory");
}
__device__ __forceinline__ void mbar_expect_tx(uint32_t bar, uint32_t bytes) {
    asm volatile("mbarrier.arrive.expect_tx.shared::cta.b64 _, [%0], %1;" :: "r"(bar), "r"(bytes) : "memory");
}
__device__ __forceinline__ void mbar_arrive(uint32_t bar) {
    asm volatile("mbarrier.arrive.shared::cta.b64 _, [%0];" :: "r"(bar) : "memory");
}
__device__ __forceinline__ void mbar_arrive_remote(uint32_t bar, uint32_t cta) {
    asm volatile("{\n.reg .b32 ra;\nmapa.shared::cluster.u32 ra, %0, %1;\n"
                 "mbarrier.arrive.shared::cluster.b64 _, [ra];\n}" :: "r"(bar), "r"(cta) : "memory");
}
__device__ __forceinline__ void mbar_wait(uint32_t bar, uint32_t parity) {
    uint32_t ok;
    int it = 0;
    do {
        asm volatile("{\n.reg .pred p;\nmbarrier.try_wait.parity.shared::cta.b64 p, [%1], %2;\nselp.u32 %0, 1, 0, p;\n}"
                     : "=r"(ok) : "r"(bar), "r"(parity) : "memory");
    } while (!ok && ++it < kSpinLimit);
}
__device__ __forceinline__ void tma_load(uint32_t dst, const CUtensorMap* tm, uint32_t bar, int row, int blk) {
    asm volatile("cp.async.bulk.tensor.3d.shared::cluster.global.mbarrier::complete_tx::bytes [%0], [%1, {%3, %4, %5}], [%2];"
                 :: "r"(dst), "l"(tm), "r"(bar), "r"(0), "r"(row), "r"(blk) : "memory");
}
__device__ __forceinline__ uint64_t policy_evict_first() {
    uint64_t p;
    asm volatile("createpolicy.fractional.L2::evict_first.b64 %0, 1.0;" : "=l"(p));
    return p;
}
__device__ __forceinline__ void tma_load_ef(uint32_t dst, const CUtensorMap* tm, uint32_t bar, int row, int blk, uint64_t pol) {
    asm volatile("cp.async.bulk.tensor.3d.shared::cluster.global.mbarrier::complete_tx::bytes.L2::cache_hint [%0], [%1, {%3, %4, %5}], [%2], %6;"
                 :: "r"(dst), "l"(tm), "r"(bar), "r"(0), "r"(row), "r"(blk), "l"(pol) : "memory");
}
__device__ __forceinline__ void tma_load_mc(uint32_t dst, const CUtensorMap* tm, uint32_t bar, int row, int blk, uint64_t pol) {
    asm volatile("cp.async.bulk.tensor.3d.shared::cluster.global.mbarrier::complete_tx::bytes.multicast::cluster.L2::cache_hint [%0], [%1, {%3, %4, %5}], [%2], %6, %7;"
                 :: "r"(dst), "l"(tm), "r"(bar), "r"(0), "r"(row), "r"(blk), "h"((uint16_t)3), "l"(pol) : "memory");
}
__device__ __forceinline__ void tma_prefetch(const CUtensorMap* tm, int row, int blk) {
    asm volatile("cp.async.bulk.prefetch.tensor.3d.L2.global.tile [%0, {%1, %2, %3}];"
                 :: "l"(tm), "r"(0), "r"(row), "r"(blk) : "memory");
}
__device__ __forceinline__ void bulk_load(uint32_t dst, const void* src, uint32_t bytes, uint32_t bar) {
    asm volatile("cp.async.bulk.shared::cluster.global.mbarrier::complete_tx::bytes [%0], [%1], %2, [%3];"
                 :: "r"(dst), "l"(src), "r"(bytes), "r"(bar) : "memory");
}
__device__ __forceinline__ void bulk_load_mc(uint32_t dst, const void* src, uint32_t bytes, uint32_t bar) {
    asm volatile("cp.async.bulk.shared::cluster.global.mbarrier::complete_tx::bytes.multicast::cluster [%0], [%1], %2, [%3], %4;"
                 :: "r"(dst), "l"(src), "r"(bytes), "r"(bar), "h"((uint16_t)3) : "memory");
}
__device__ __forceinline__ void bulk_push(uint32_t dst, uint32_t src, uint32_t bytes, uint32_t bar, uint32_t cta) {
    asm volatile("{\n.reg .b32 rd, rb;\nmapa.shared::cluster.u32 rd, %0, %4;\nmapa.shared::cluster.u32 rb, %3, %4;\n"
                 "cp.async.bulk.shared::cluster.shared::cta.mbarrier::complete_tx::bytes [rd], [%1], %2, [rb];\n}"
                 :: "r"(dst), "r"(src), "r"(bytes), "r"(bar), "r"(cta) : "memory");
}
__device__ __forceinline__ void wg_fence() { asm volatile("wgmma.fence.sync.aligned;" ::: "memory"); }
__device__ __forceinline__ void wg_commit() { asm volatile("wgmma.commit_group.sync.aligned;" ::: "memory"); }
template <int N> __device__ __forceinline__ void wg_wait() { asm volatile("wgmma.wait_group.sync.aligned %0;" :: "n"(N) : "memory"); }

__device__ __forceinline__ uint64_t desc_sw128(uint32_t addr, uint32_t lbo) {
    return (uint64_t)((addr & 0x3FFFF) >> 4) | ((uint64_t)(lbo >> 4) << 16) | ((uint64_t)(1024 >> 4) << 32) | (1ull << 62);
}
__device__ __forceinline__ uint32_t pack_bf16(float lo, float hi) {
    uint32_t r;
    asm("cvt.rn.bf16x2.f32 %0, %1, %2;" : "=r"(r) : "f"(hi), "f"(lo));
    return r;
}
__device__ __forceinline__ float ex2(float x) {
    float y;
    asm("ex2.approx.ftz.f32 %0, %1;" : "=f"(y) : "f"(x));
    return y;
}
__device__ __forceinline__ unsigned ld_relaxed_gpu(const unsigned* p) {
    unsigned v;
    asm volatile("ld.relaxed.gpu.global.u32 %0, [%1];" : "=r"(v) : "l"(p) : "memory");
    return v;
}
__device__ __forceinline__ void fence_gpu() { asm volatile("fence.acq_rel.gpu;" ::: "memory"); }
__device__ __forceinline__ void red_add_u32(unsigned* p, unsigned v) {
    asm volatile("red.relaxed.gpu.global.add.u32 [%0], %1;" :: "l"(p), "r"(v) : "memory");
}
__device__ __forceinline__ unsigned ld_acquire_gpu(const unsigned* p) {
    unsigned v;
    asm volatile("ld.acquire.gpu.global.u32 %0, [%1];" : "=r"(v) : "l"(p) : "memory");
    return v;
}
__device__ __forceinline__ void spin_flag(const unsigned* p, unsigned target) {
    int it = 0;
    while ((int)(ld_acquire_gpu(p) - target) < 0 && ++it < kSpinLimit) {}
}
template <int R> __device__ __forceinline__ void reg_alloc() { asm volatile("setmaxnreg.inc.sync.aligned.u32 %0;" :: "n"(R)); }
template <int R> __device__ __forceinline__ void reg_dealloc() { asm volatile("setmaxnreg.dec.sync.aligned.u32 %0;" :: "n"(R)); }

__device__ __forceinline__ void wgmma_n64_ss(float (&d)[32], uint64_t da, uint64_t db, int scale_d) {
    asm volatile("{\n.reg .pred p;\nsetp.ne.b32 p, %34, 0;\n"
        "wgmma.mma_async.sync.aligned.m64n64k16.f32.bf16.bf16 "
        "{%0, %1, %2, %3, %4, %5, %6, %7, %8, %9, %10, %11, %12, %13, %14, %15, "
        "%16, %17, %18, %19, %20, %21, %22, %23, %24, %25, %26, %27, %28, %29, %30, %31}, "
        "%32, %33, p, 1, 1, 0, 0;\n}\n"
        : "+f"(d[0]), "+f"(d[1]), "+f"(d[2]), "+f"(d[3]), "+f"(d[4]), "+f"(d[5]), "+f"(d[6]), "+f"(d[7]),
          "+f"(d[8]), "+f"(d[9]), "+f"(d[10]), "+f"(d[11]), "+f"(d[12]), "+f"(d[13]), "+f"(d[14]), "+f"(d[15]),
          "+f"(d[16]), "+f"(d[17]), "+f"(d[18]), "+f"(d[19]), "+f"(d[20]), "+f"(d[21]), "+f"(d[22]), "+f"(d[23]),
          "+f"(d[24]), "+f"(d[25]), "+f"(d[26]), "+f"(d[27]), "+f"(d[28]), "+f"(d[29]), "+f"(d[30]), "+f"(d[31])
        : "l"(da), "l"(db), "r"(scale_d));
}
__device__ __forceinline__ void wgmma_n64_rs_tb(float (&d)[32], uint32_t a0, uint32_t a1, uint32_t a2, uint32_t a3, uint64_t db, int scale_d) {
    asm volatile("{\n.reg .pred p;\nsetp.ne.b32 p, %37, 0;\n"
        "wgmma.mma_async.sync.aligned.m64n64k16.f32.bf16.bf16 "
        "{%0, %1, %2, %3, %4, %5, %6, %7, %8, %9, %10, %11, %12, %13, %14, %15, "
        "%16, %17, %18, %19, %20, %21, %22, %23, %24, %25, %26, %27, %28, %29, %30, %31}, "
        "{%32, %33, %34, %35}, %36, p, 1, 1, 1;\n}\n"
        : "+f"(d[0]), "+f"(d[1]), "+f"(d[2]), "+f"(d[3]), "+f"(d[4]), "+f"(d[5]), "+f"(d[6]), "+f"(d[7]),
          "+f"(d[8]), "+f"(d[9]), "+f"(d[10]), "+f"(d[11]), "+f"(d[12]), "+f"(d[13]), "+f"(d[14]), "+f"(d[15]),
          "+f"(d[16]), "+f"(d[17]), "+f"(d[18]), "+f"(d[19]), "+f"(d[20]), "+f"(d[21]), "+f"(d[22]), "+f"(d[23]),
          "+f"(d[24]), "+f"(d[25]), "+f"(d[26]), "+f"(d[27]), "+f"(d[28]), "+f"(d[29]), "+f"(d[30]), "+f"(d[31])
        : "r"(a0), "r"(a1), "r"(a2), "r"(a3), "l"(db), "r"(scale_d));
}
__device__ __forceinline__ void wgmma_n128_rs(float (&d)[64], uint32_t a0, uint32_t a1, uint32_t a2, uint32_t a3, uint64_t db, int scale_d) {
    asm volatile("{\n.reg .pred p;\nsetp.ne.b32 p, %69, 0;\n"
        "wgmma.mma_async.sync.aligned.m64n128k16.f32.bf16.bf16 "
        "{%0, %1, %2, %3, %4, %5, %6, %7, %8, %9, %10, %11, %12, %13, %14, %15, "
        "%16, %17, %18, %19, %20, %21, %22, %23, %24, %25, %26, %27, %28, %29, %30, %31, "
        "%32, %33, %34, %35, %36, %37, %38, %39, %40, %41, %42, %43, %44, %45, %46, %47, "
        "%48, %49, %50, %51, %52, %53, %54, %55, %56, %57, %58, %59, %60, %61, %62, %63}, "
        "{%64, %65, %66, %67}, %68, p, 1, 1, 0;\n}\n"
        : "+f"(d[0]), "+f"(d[1]), "+f"(d[2]), "+f"(d[3]), "+f"(d[4]), "+f"(d[5]), "+f"(d[6]), "+f"(d[7]),
          "+f"(d[8]), "+f"(d[9]), "+f"(d[10]), "+f"(d[11]), "+f"(d[12]), "+f"(d[13]), "+f"(d[14]), "+f"(d[15]),
          "+f"(d[16]), "+f"(d[17]), "+f"(d[18]), "+f"(d[19]), "+f"(d[20]), "+f"(d[21]), "+f"(d[22]), "+f"(d[23]),
          "+f"(d[24]), "+f"(d[25]), "+f"(d[26]), "+f"(d[27]), "+f"(d[28]), "+f"(d[29]), "+f"(d[30]), "+f"(d[31]),
          "+f"(d[32]), "+f"(d[33]), "+f"(d[34]), "+f"(d[35]), "+f"(d[36]), "+f"(d[37]), "+f"(d[38]), "+f"(d[39]),
          "+f"(d[40]), "+f"(d[41]), "+f"(d[42]), "+f"(d[43]), "+f"(d[44]), "+f"(d[45]), "+f"(d[46]), "+f"(d[47]),
          "+f"(d[48]), "+f"(d[49]), "+f"(d[50]), "+f"(d[51]), "+f"(d[52]), "+f"(d[53]), "+f"(d[54]), "+f"(d[55]),
          "+f"(d[56]), "+f"(d[57]), "+f"(d[58]), "+f"(d[59]), "+f"(d[60]), "+f"(d[61]), "+f"(d[62]), "+f"(d[63])
        : "r"(a0), "r"(a1), "r"(a2), "r"(a3), "l"(db), "r"(scale_d));
}
__device__ __forceinline__ void wgmma_n256_rs_tb(float (&d)[128], uint32_t a0, uint32_t a1, uint32_t a2, uint32_t a3, uint64_t db, int scale_d) {
    asm volatile("{\n.reg .pred p;\nsetp.ne.b32 p, %133, 0;\n"
        "wgmma.mma_async.sync.aligned.m64n256k16.f32.bf16.bf16 "
        "{%0, %1, %2, %3, %4, %5, %6, %7, %8, %9, %10, %11, %12, %13, %14, %15, "
        "%16, %17, %18, %19, %20, %21, %22, %23, %24, %25, %26, %27, %28, %29, %30, %31, "
        "%32, %33, %34, %35, %36, %37, %38, %39, %40, %41, %42, %43, %44, %45, %46, %47, "
        "%48, %49, %50, %51, %52, %53, %54, %55, %56, %57, %58, %59, %60, %61, %62, %63, "
        "%64, %65, %66, %67, %68, %69, %70, %71, %72, %73, %74, %75, %76, %77, %78, %79, "
        "%80, %81, %82, %83, %84, %85, %86, %87, %88, %89, %90, %91, %92, %93, %94, %95, "
        "%96, %97, %98, %99, %100, %101, %102, %103, %104, %105, %106, %107, %108, %109, %110, %111, "
        "%112, %113, %114, %115, %116, %117, %118, %119, %120, %121, %122, %123, %124, %125, %126, %127}, "
        "{%128, %129, %130, %131}, %132, p, 1, 1, 1;\n}\n"
        : "+f"(d[0]), "+f"(d[1]), "+f"(d[2]), "+f"(d[3]), "+f"(d[4]), "+f"(d[5]), "+f"(d[6]), "+f"(d[7]),
          "+f"(d[8]), "+f"(d[9]), "+f"(d[10]), "+f"(d[11]), "+f"(d[12]), "+f"(d[13]), "+f"(d[14]), "+f"(d[15]),
          "+f"(d[16]), "+f"(d[17]), "+f"(d[18]), "+f"(d[19]), "+f"(d[20]), "+f"(d[21]), "+f"(d[22]), "+f"(d[23]),
          "+f"(d[24]), "+f"(d[25]), "+f"(d[26]), "+f"(d[27]), "+f"(d[28]), "+f"(d[29]), "+f"(d[30]), "+f"(d[31]),
          "+f"(d[32]), "+f"(d[33]), "+f"(d[34]), "+f"(d[35]), "+f"(d[36]), "+f"(d[37]), "+f"(d[38]), "+f"(d[39]),
          "+f"(d[40]), "+f"(d[41]), "+f"(d[42]), "+f"(d[43]), "+f"(d[44]), "+f"(d[45]), "+f"(d[46]), "+f"(d[47]),
          "+f"(d[48]), "+f"(d[49]), "+f"(d[50]), "+f"(d[51]), "+f"(d[52]), "+f"(d[53]), "+f"(d[54]), "+f"(d[55]),
          "+f"(d[56]), "+f"(d[57]), "+f"(d[58]), "+f"(d[59]), "+f"(d[60]), "+f"(d[61]), "+f"(d[62]), "+f"(d[63]),
          "+f"(d[64]), "+f"(d[65]), "+f"(d[66]), "+f"(d[67]), "+f"(d[68]), "+f"(d[69]), "+f"(d[70]), "+f"(d[71]),
          "+f"(d[72]), "+f"(d[73]), "+f"(d[74]), "+f"(d[75]), "+f"(d[76]), "+f"(d[77]), "+f"(d[78]), "+f"(d[79]),
          "+f"(d[80]), "+f"(d[81]), "+f"(d[82]), "+f"(d[83]), "+f"(d[84]), "+f"(d[85]), "+f"(d[86]), "+f"(d[87]),
          "+f"(d[88]), "+f"(d[89]), "+f"(d[90]), "+f"(d[91]), "+f"(d[92]), "+f"(d[93]), "+f"(d[94]), "+f"(d[95]),
          "+f"(d[96]), "+f"(d[97]), "+f"(d[98]), "+f"(d[99]), "+f"(d[100]), "+f"(d[101]), "+f"(d[102]), "+f"(d[103]),
          "+f"(d[104]), "+f"(d[105]), "+f"(d[106]), "+f"(d[107]), "+f"(d[108]), "+f"(d[109]), "+f"(d[110]), "+f"(d[111]),
          "+f"(d[112]), "+f"(d[113]), "+f"(d[114]), "+f"(d[115]), "+f"(d[116]), "+f"(d[117]), "+f"(d[118]), "+f"(d[119]),
          "+f"(d[120]), "+f"(d[121]), "+f"(d[122]), "+f"(d[123]), "+f"(d[124]), "+f"(d[125]), "+f"(d[126]), "+f"(d[127])
        : "r"(a0), "r"(a1), "r"(a2), "r"(a3), "l"(db), "r"(scale_d));
}
__device__ __forceinline__ void wgmma_n72_rs_tb(float (&d)[36], uint32_t a0, uint32_t a1, uint32_t a2, uint32_t a3, uint64_t db, int scale_d) {
    asm volatile("{\n.reg .pred p;\nsetp.ne.b32 p, %41, 0;\n"
        "wgmma.mma_async.sync.aligned.m64n72k16.f32.bf16.bf16 "
        "{%0, %1, %2, %3, %4, %5, %6, %7, %8, %9, %10, %11, %12, %13, %14, %15, "
        "%16, %17, %18, %19, %20, %21, %22, %23, %24, %25, %26, %27, %28, %29, %30, %31, "
        "%32, %33, %34, %35}, "
        "{%36, %37, %38, %39}, %40, p, 1, 1, 1;\n}\n"
        : "+f"(d[0]), "+f"(d[1]), "+f"(d[2]), "+f"(d[3]), "+f"(d[4]), "+f"(d[5]), "+f"(d[6]), "+f"(d[7]),
          "+f"(d[8]), "+f"(d[9]), "+f"(d[10]), "+f"(d[11]), "+f"(d[12]), "+f"(d[13]), "+f"(d[14]), "+f"(d[15]),
          "+f"(d[16]), "+f"(d[17]), "+f"(d[18]), "+f"(d[19]), "+f"(d[20]), "+f"(d[21]), "+f"(d[22]), "+f"(d[23]),
          "+f"(d[24]), "+f"(d[25]), "+f"(d[26]), "+f"(d[27]), "+f"(d[28]), "+f"(d[29]), "+f"(d[30]), "+f"(d[31]),
          "+f"(d[32]), "+f"(d[33]), "+f"(d[34]), "+f"(d[35])
        : "r"(a0), "r"(a1), "r"(a2), "r"(a3), "l"(db), "r"(scale_d));
}

constexpr float kC1 = 0.25f * 1.4426950408889634f;
constexpr float kC2 = -1.4426950408889634f / 32.0f;
constexpr float kC3 = -4.0f;

__device__ __forceinline__ uint32_t slot_addr(uint32_t sb, int s) { return sb + SM_SLOT + (s < 3 ? s + 2 : s - 3) * SLOT_BYTES; }
__device__ __forceinline__ uint32_t bar_addr(uint32_t sb, int b) { return sb + SM_BAR + b * 8; }

__device__ __forceinline__ void release_pair(uint32_t bar, uint32_t rank) {
    mbar_arrive(bar);
    mbar_arrive_remote(bar, rank ^ 1);
}

__device__ __forceinline__ float row_bias(uint32_t tile, int row, int half) {
    const uint32_t base = tile + half * 16384 + row * 128;
    const uint32_t sw = ((row & 7) ^ (half << 2)) << 4;
    float s0 = 0.f, s1 = 0.f, s2 = 0.f, s3 = 0.f;
#pragma unroll
    for (int bt = 0; bt < 4; bt++) {
        uint32_t x[4][4];
#pragma unroll
        for (int i = 0; i < 4; i++)
            asm volatile("ld.shared.v4.u32 {%0, %1, %2, %3}, [%4];" : "=r"(x[i][0]), "=r"(x[i][1]), "=r"(x[i][2]), "=r"(x[i][3])
                         : "r"(base + (bt >> 1) * 8192 + ((((bt & 1) * 4 + i) << 4) ^ sw)));
#pragma unroll
        for (int i = 0; i < 4; i++) {
            float a;
            a = __uint_as_float(x[i][0] << 16); s0 = fmaf(a, a, s0);
            a = __uint_as_float(x[i][0] & 0xffff0000u); s1 = fmaf(a, a, s1);
            a = __uint_as_float(x[i][1] << 16); s2 = fmaf(a, a, s2);
            a = __uint_as_float(x[i][1] & 0xffff0000u); s3 = fmaf(a, a, s3);
            a = __uint_as_float(x[i][2] << 16); s0 = fmaf(a, a, s0);
            a = __uint_as_float(x[i][2] & 0xffff0000u); s1 = fmaf(a, a, s1);
            a = __uint_as_float(x[i][3] << 16); s2 = fmaf(a, a, s2);
            a = __uint_as_float(x[i][3] & 0xffff0000u); s3 = fmaf(a, a, s3);
        }
    }
    float s = (s0 + s1) + (s2 + s3);
    s += __shfl_xor_sync(0xffffffffu, s, 1);
    return fmaf(s, kC2, kC3);
}
__device__ __forceinline__ void st_async_f32(uint32_t addr, float v, uint32_t bar, uint32_t cta) {
    asm volatile("{\n.reg .b32 ra, rb;\nmapa.shared::cluster.u32 ra, %0, %3;\nmapa.shared::cluster.u32 rb, %2, %3;\n"
                 "st.async.weak.shared::cluster.mbarrier::complete_tx::bytes.f32 [ra], %1, [rb];\n}"
                 :: "r"(addr), "f"(v), "r"(bar), "r"(cta) : "memory");
}

__device__ __forceinline__ void load_q_frags(uint32_t (&f)[64], float& qb0, float& qb1, uint32_t tile, int wq, int lane) {
    const int row = wq * 16 + (lane & 7) + ((lane >> 3) & 1) * 8;
    const uint32_t base = tile + row * 128;
#pragma unroll
    for (int k = 0; k < 16; k++) {
        const int chunk = 2 * k + (lane >> 4);
        asm volatile("ldmatrix.sync.aligned.m8n8.x4.shared.b16 {%0, %1, %2, %3}, [%4];"
                     : "=r"(f[4 * k]), "=r"(f[4 * k + 1]), "=r"(f[4 * k + 2]), "=r"(f[4 * k + 3])
                     : "r"(base + (k >> 2) * 8192 + (((chunk & 7) ^ (row & 7)) << 4)));
    }
    float s0 = 0.f, s1 = 0.f, s2 = 0.f, s3 = 0.f;
#pragma unroll
    for (int k = 0; k < 32; k++) {
        float a;
        a = __uint_as_float(f[2 * k] << 16); s0 = fmaf(a, a, s0);
        a = __uint_as_float(f[2 * k] & 0xffff0000u); s1 = fmaf(a, a, s1);
        a = __uint_as_float(f[2 * k + 1] << 16); s2 = fmaf(a, a, s2);
        a = __uint_as_float(f[2 * k + 1] & 0xffff0000u); s3 = fmaf(a, a, s3);
    }
    s0 += s1; s2 += s3;
    s0 += __shfl_xor_sync(0xffffffffu, s0, 1); s2 += __shfl_xor_sync(0xffffffffu, s2, 1);
    s0 += __shfl_xor_sync(0xffffffffu, s0, 2); s2 += __shfl_xor_sync(0xffffffffu, s2, 2);
    qb0 = fmaf(s0, kC2, kC3);
    qb1 = fmaf(s2, kC2, kC3);
}
__device__ __forceinline__ void gemm3(float (&d)[64], const uint32_t (&f)[64], uint32_t b01, uint32_t b23) {
    const uint64_t d0 = desc_sw128(b01, 16), d1 = desc_sw128(b23, 16);
    wg_fence();
#pragma unroll
    for (int k = 0; k < 16; k++)
        wgmma_n128_rs(d, f[4 * k], f[4 * k + 1], f[4 * k + 2], f[4 * k + 3],
                      (k < 8 ? d0 : d1) + ((((k >> 2) & 1) * 16384 + (k & 3) * 32) >> 4), k > 0);
    wg_commit();
}
template <int O>
__device__ __forceinline__ void exp_to_regs(uint32_t (&phi)[64], const float (&a)[64], float qb0, float qb1) {
#pragma unroll
    for (int j = 0; j < 16; j++) {
        phi[O + 2 * j] = pack_bf16(ex2(fmaf(a[4 * j], kC1, qb0)), ex2(fmaf(a[4 * j + 1], kC1, qb0)));
        phi[O + 2 * j + 1] = pack_bf16(ex2(fmaf(a[4 * j + 2], kC1, qb1)), ex2(fmaf(a[4 * j + 3], kC1, qb1)));
    }
}
template <int HF>
__device__ __forceinline__ void exp_to_smem(uint32_t tile, const float (&a)[64], float qb0, float qb1, int wq, int lane) {
    const int srow = wq * 16 + ((lane >> 3) & 1) * 8 + (lane & 7);
    const uint32_t sbase = tile + srow * 128;
#pragma unroll
    for (int jp = 0; jp < 8; jp++) {
        const int j = 2 * jp;
        const uint32_t r0 = pack_bf16(ex2(fmaf(a[4 * j], kC1, qb0)), ex2(fmaf(a[4 * j + 1], kC1, qb0)));
        const uint32_t r1 = pack_bf16(ex2(fmaf(a[4 * j + 2], kC1, qb1)), ex2(fmaf(a[4 * j + 3], kC1, qb1)));
        const uint32_t r2 = pack_bf16(ex2(fmaf(a[4 * j + 4], kC1, qb0)), ex2(fmaf(a[4 * j + 5], kC1, qb0)));
        const uint32_t r3 = pack_bf16(ex2(fmaf(a[4 * j + 6], kC1, qb1)), ex2(fmaf(a[4 * j + 7], kC1, qb1)));
        const int chunk = HF * 16 + j + (lane >> 4);
        asm volatile("stmatrix.sync.aligned.m8n8.x4.shared.b16 [%0], {%1, %2, %3, %4};"
                     :: "r"(sbase + (chunk >> 3) * 8192 + (((chunk & 7) ^ (srow & 7)) << 4)), "r"(r0), "r"(r1), "r"(r2), "r"(r3) : "memory");
    }
}
template <int ID> __device__ __forceinline__ void bar_sync() { asm volatile("bar.sync %0, 256;" :: "n"(ID) : "memory"); }
template <int ID> __device__ __forceinline__ void bar_arrive() { asm volatile("bar.arrive %0, 256;" :: "n"(ID) : "memory"); }

template <int N>
__device__ __forceinline__ void store_out(const float (&o)[N], float inv0, float inv1, __nv_bfloat16* p0) {
#pragma unroll
    for (int t = 0; t < 2; t++) {
#pragma unroll
        for (int i = 0; i < 2; i++) {
            const float inv = i ? inv1 : inv0;
            uint4 v;
            v.x = pack_bf16(o[16 * t + 2 * i] * inv, o[16 * t + 2 * i + 1] * inv);
            v.y = pack_bf16(o[16 * t + 4 + 2 * i] * inv, o[16 * t + 4 + 2 * i + 1] * inv);
            v.z = pack_bf16(o[16 * t + 8 + 2 * i] * inv, o[16 * t + 8 + 2 * i + 1] * inv);
            v.w = pack_bf16(o[16 * t + 12 + 2 * i] * inv, o[16 * t + 12 + 2 * i + 1] * inv);
            if (!ABL_NOOUT || v.x == 0x12345678u) *reinterpret_cast<uint4*>(p0 + i * 8 * kDim + t * 32) = v;
        }
    }
}

__global__ void __cluster_dims__(2, 1, 1) __launch_bounds__(384, 1)
performer_kernel(const __grid_constant__ CUtensorMap tm_q, const __grid_constant__ CUtensorMap tm_k,
                 const __grid_constant__ CUtensorMap tm_v, const __grid_constant__ CUtensorMap tm_p,
                 const uint8_t* __restrict__ qptr, const uint8_t* __restrict__ kptr, const uint8_t* __restrict__ vptr, const uint8_t* __restrict__ pptr,
                 __nv_bfloat16* __restrict__ out) {
    extern __shared__ __align__(1024) uint8_t smem[];
    const uint32_t sb = (uint32_t)__cvta_generic_to_shared(smem);
    const int tid = threadIdx.x, lane = tid & 31;
    const int warp = __shfl_sync(0xffffffffu, tid >> 5, 0);
    uint32_t rank;
    asm volatile("mov.u32 %0, %%cluster_ctarank;" : "=r"(rank));
    const int cta = blockIdx.x, pair = cta >> 1, h = pair >> 2, sc = pair & 3;

    if (tid == 64) {
        const size_t off = (size_t)(h * kSeq + sc * 512 + rank * 32) * 512;
#pragma unroll
        for (int i = 0; i < EARLY_PF; i++)
            asm volatile("cp.async.bulk.prefetch.L2.global [%0], %1;"
                         :: "l"(((i & 1) ? vptr : kptr) + off + (i >> 1) * 32768), "r"(16384) : "memory");
        asm volatile("cp.async.bulk.prefetch.L2.global [%0], %1;" :: "l"(pptr + cta * 1024), "r"(1024) : "memory");
    }
    if (tid == 32) {
        asm volatile("prefetch.tensormap [%0];" :: "l"(&tm_p) : "memory");
        asm volatile("prefetch.tensormap [%0];" :: "l"(&tm_k) : "memory");
        asm volatile("prefetch.tensormap [%0];" :: "l"(&tm_v) : "memory");
        asm volatile("prefetch.tensormap [%0];" :: "l"(&tm_q) : "memory");
    }
    if (tid == 0) {
        PROF(0);
        mbar_init(bar_addr(sb, B_PROJ), 1);
#pragma unroll
        for (int i = 0; i < 3; i++) { mbar_init(bar_addr(sb, B_KFULL + i), 1); mbar_init(bar_addr(sb, B_KEMPTY + i), 20); }
#pragma unroll
        for (int i = 0; i < 2; i++) { mbar_init(bar_addr(sb, B_VFULL + i), 1); mbar_init(bar_addr(sb, B_VEMPTY + i), 16); }
#pragma unroll
        for (int i = 0; i < 4; i++) { mbar_init(bar_addr(sb, B_KV + i), 1); mbar_init(bar_addr(sb, B_NORM + i), 1); }
        mbar_init(bar_addr(sb, B_PO01), 1);
        mbar_init(bar_addr(sb, B_PO23), 1);
        mbar_init(bar_addr(sb, B_ZERO), 1);
#pragma unroll
        for (int i = 0; i < 2; i++) {
            mbar_init(bar_addr(sb, B_STG + i), 4);
            mbar_init(bar_addr(sb, B_SFREE + i), 1 + i * KV_MC);
            mbar_init(bar_addr(sb, B_ACONS + i), 4);
        }
        mbar_init(bar_addr(sb, B_PDEAD), KV_MC ? 16 : 8);
        mbar_init(bar_addr(sb, B_KSUM), 1);
        mbar_init(bar_addr(sb, B_DUMPED), 1);
        asm volatile("fence.mbarrier_init.release.cluster;" ::: "memory");
        mbar_expect_tx(bar_addr(sb, B_PROJ), 65536);
        tma_load(sb + SM_P0, &tm_p, bar_addr(sb, B_PROJ), rank * 128, 0);
        tma_load(sb + SM_P0 + 32768, &tm_p, bar_addr(sb, B_PROJ), rank * 128, 2);
    }
    asm volatile("barrier.cluster.arrive.relaxed.aligned;" ::: "memory");
    asm volatile("barrier.cluster.wait.aligned;" ::: "memory");

    if (warp < 4) {
        reg_dealloc<40>();
        if (warp == 0) {
            if (lane == 0) {
                const int row0 = h * kSeq + sc * 512;
                const uint64_t pol = policy_evict_first();
                auto load_k = [&](int t) {
                    const int s = t % 3;
                    if (t >= 3) mbar_wait(bar_addr(sb, B_KEMPTY + s), (t / 3 - 1) & 1);
                    mbar_expect_tx(bar_addr(sb, B_KFULL + s), SLOT_BYTES);
                    tma_load_mc(slot_addr(sb, s) + rank * 16384, &tm_k, bar_addr(sb, B_KFULL + s), row0 + t * 64, rank * 2, pol);
                };
                auto load_v = [&](int t) {
                    const int s = t & 1;
                    if (t >= 2) mbar_wait(bar_addr(sb, B_VEMPTY + s), (t / 2 - 1) & 1);
                    mbar_expect_tx(bar_addr(sb, B_VFULL + s), SLOT_BYTES);
                    tma_load_mc(slot_addr(sb, 3 + s) + rank * 16384, &tm_v, bar_addr(sb, B_VFULL + s), row0 + t * 64, rank * 2, pol);
                };
                PROFS(1);
                load_k(0);
                load_v(0);
                load_k(1);
                load_v(1);
                load_k(2);
                PROFS(2);
#pragma unroll 1
                for (int t = 2; t < 7; t++) { load_k(t + 1); load_v(t); }
                load_v(7);
                CLKP(0);
                const int qrow = row0 + rank * 256;
                auto load_q = [&](int piece, int slot, int fullbar) {
                    mbar_expect_tx(bar_addr(sb, fullbar), SLOT_BYTES);
                    tma_load_ef(slot_addr(sb, slot), &tm_q, bar_addr(sb, fullbar), qrow + piece * 64, 0, pol);
                    tma_load_ef(slot_addr(sb, slot) + 16384, &tm_q, bar_addr(sb, fullbar), qrow + piece * 64, 2, pol);
                };
                mbar_wait(bar_addr(sb, B_KEMPTY + 2), 1);
                mbar_wait(bar_addr(sb, B_KEMPTY + 0), 0);
                mbar_expect_tx(bar_addr(sb, B_PO23), SLOT_BYTES);
                tma_load(slot_addr(sb, 0), &tm_p, bar_addr(sb, B_PO23), (rank ^ 1) * 128, 2);
                CLKP(1);
                mbar_wait(bar_addr(sb, B_KFULL + 1), 0);
                load_q(0, 2, B_KFULL + 2);
                mbar_wait(bar_addr(sb, B_VEMPTY + 0), 1);
                CLKP(3);
                mbar_expect_tx(bar_addr(sb, B_PO01), SLOT_BYTES);
                tma_load(slot_addr(sb, 3), &tm_p, bar_addr(sb, B_PO01), (rank ^ 1) * 128, 0);
                mbar_wait(bar_addr(sb, B_KEMPTY + 1), 0);
                load_q(1, 1, B_KFULL + 1);
                CLKP(4);
                mbar_wait(bar_addr(sb, B_ACONS + 0), 0);
                load_q(2, 2, B_KFULL + 2);
                CLKP(7);
                mbar_wait(bar_addr(sb, B_ACONS + 1), 0);
                load_q(3, 1, B_KFULL + 1);
                CLKP(8);
            }
            __syncwarp();
        } else if (warp < 3) {
            const int w = warp - 1;
            const int row = rank * 32 + w * 16 + (lane >> 1);
#pragma unroll 1
            for (int t = 0; t < 8; t++) {
                const int s = t % 3;
                const uint32_t nbar = bar_addr(sb, B_NORM + (t & 3));
                if (w == 0 && lane == 0) mbar_expect_tx(nbar, 256);
                mbar_wait(bar_addr(sb, B_KFULL + s), (t / 3) & 1);
                const float b = row_bias(slot_addr(sb, s), row, lane & 1);
                if (!(lane & 1)) {
                    const uint32_t dst = sb + SM_NORM + (t & 3) * 256 + row * 4;
                    st_async_f32(dst, b, nbar, 0);
                    st_async_f32(dst, b, nbar, 1);
                }
                __syncwarp();
                if (lane == 0) release_pair(bar_addr(sb, B_KEMPTY + s), rank);
            }
            if (w == 0 && lane == 0) {
                const uint32_t src = slot_addr(sb, 4);
                mbar_wait(bar_addr(sb, B_ZERO), 0);
#pragma unroll 1
                for (int g2 = 0; g2 < 2; g2++) {
                    uint8_t* dst = reinterpret_cast<uint8_t*>(g_kvacc + h * 8192) + (rank * 128 + g2 * 64) * 128;
                    mbar_wait(bar_addr(sb, B_STG + g2), 0);
                    CLKP(17 + g2);
                    asm volatile("fence.proxy.async.global;" ::: "memory");
                    asm volatile("cp.reduce.async.bulk.global.shared::cta.bulk_group.add.f32 [%0], [%1], %2;"
                                 :: "l"(g_ksum + h * 256 + rank * 128 + g2 * 64), "r"(sb + SM_KS + g2 * 256), "r"(256) : "memory");
#pragma unroll 1
                    for (int b = 0; b < (ABL_NORED ? 0 : 8); b++) {
                        asm volatile("cp.reduce.async.bulk.global.shared::cta.bulk_group.add.noftz.bf16 [%0], [%1], %2;"
                                     :: "l"(dst + (b >> 1) * 32768 + (b & 1) * 4096), "r"(src + b * 4096), "r"(4096) : "memory");
                        asm volatile("cp.async.bulk.commit_group;" ::: "memory");
                        asm volatile("cp.async.bulk.wait_group.read 0;" ::: "memory");
                    }
                    if (g2 == 0 || !KV_MC) mbar_arrive(bar_addr(sb, B_SFREE + g2)); else release_pair(bar_addr(sb, B_SFREE + 1), rank);
                    CLKP(9 + g2);
                }
                asm volatile("cp.async.bulk.wait_group 0;" ::: "memory");
                CLKP(12);
                asm volatile("fence.proxy.async.global;" ::: "memory");
                CLKP(14);
                red_add_u32(&g_flag_dump[h * 32], 1);
                mbar_arrive(bar_addr(sb, B_DUMPED));
            }
            __syncwarp();
        } else {
            unsigned target = 0;
            if (lane == 0) target = ld_relaxed_gpu(&g_flag_dump[h * 32]) + 8;
            uint4* z = g_kvacc + h * 8192 + (cta & 7) * 1024;
#pragma unroll 4
            for (int i = 0; i < 32; i++) z[i * 32 + lane] = make_uint4(0, 0, 0, 0);
            g_ksum[h * 256 + (cta & 7) * 32 + lane] = 0.f;
            __syncwarp();
            if (lane == 0) {
                fence_gpu();
                red_add_u32(&g_flag_zero[h * 32], 1);
                spin_flag(&g_flag_zero[h * 32], target);
                asm volatile("fence.proxy.async.global;" ::: "memory");
                mbar_arrive(bar_addr(sb, B_ZERO));
                mbar_wait(bar_addr(sb, B_DUMPED), 0);
                spin_flag(&g_flag_dump[h * 32], target);
                asm volatile("fence.proxy.async.global;" ::: "memory");
                CLKP(15);
                const uint8_t* kvsrc = reinterpret_cast<const uint8_t*>(g_kvacc + h * 8192);
                mbar_expect_tx(bar_addr(sb, B_KV + 0), SLOT_BYTES);
                bulk_load(slot_addr(sb, 4), kvsrc, SLOT_BYTES, bar_addr(sb, B_KV + 0));
            }
            __syncwarp();
            uint32_t kb[8];
#pragma unroll
            for (int i = 0; i < 8; i++) {
                const float v = __ldcg(g_ksum + h * 256 + i * 32 + lane);
                kb[i] = pack_bf16(v, v);
            }
            mbar_wait(bar_addr(sb, B_PDEAD), 0);
            if (lane == 0) {
                const uint8_t* kvsrc = reinterpret_cast<const uint8_t*>(g_kvacc + h * 8192);
                mbar_expect_tx(bar_addr(sb, B_KV + 1), SLOT_BYTES);
                bulk_load(sb + SM_P0, kvsrc + 32768, SLOT_BYTES, bar_addr(sb, B_KV + 1));
                mbar_expect_tx(bar_addr(sb, B_KV + 2), SLOT_BYTES);
                bulk_load(sb + SM_P0 + 32768, kvsrc + 65536, SLOT_BYTES, bar_addr(sb, B_KV + 2));
                mbar_expect_tx(bar_addr(sb, B_KV + 3), SLOT_BYTES);
                bulk_load(slot_addr(sb, 3), kvsrc + 98304, SLOT_BYTES, bar_addr(sb, B_KV + 3));
            }
            __syncwarp();
#pragma unroll
            for (int i = 0; i < 8; i++) {
                const int m = i * 32 + lane;
                asm volatile("st.shared.v4.u32 [%0], {%1, %1, %1, %1};" :: "r"(slot_addr(sb, 0) + m * 128 + ((m & 7) << 4)), "r"(kb[i]) : "memory");
            }
            asm volatile("fence.proxy.async.shared::cta;" ::: "memory");
            __syncwarp();
            if (lane == 0) {
                mbar_arrive(bar_addr(sb, B_KSUM));
                CLKP(16);
            }
            __syncwarp();
        }
        asm volatile("barrier.cluster.arrive.relaxed.aligned;" ::: "memory");
        asm volatile("barrier.cluster.wait.aligned;" ::: "memory");
    } else {
        reg_alloc<232>();
        const int w = (warp - 4) >> 2, wq = warp & 3, g = lane >> 2, c = lane & 3;
        float ks0 = 0.f, ks1 = 0.f, qb0, qb1;
        uint32_t f[64];
        {
            float acc[128];
            uint32_t p[16];
            const uint64_t dp = desc_sw128(sb + SM_P0 + w * 8192, 16);
            mbar_wait(bar_addr(sb, B_PROJ), 0);
            PROFA(0); CLKS(28);
            int ks = 0, kph = 0;
#pragma unroll 1
            for (int t = 0; t < 8; t++) {
                float s[32];
                CLK(0);
                if (w == 1) bar_sync<2>(); else if (t > 0) bar_sync<3>();
                CLK(1);
                if (t > 0) {
                    mbar_wait(bar_addr(sb, B_VFULL + ((t - 1) & 1)), ((t - 1) >> 1) & 1);
                    const uint64_t dv = desc_sw128(slot_addr(sb, 3 + ((t - 1) & 1)), 8192);
                    wg_fence();
#pragma unroll
                    for (int k = 0; k < 4; k++)
                        wgmma_n256_rs_tb(acc, p[4 * k], p[4 * k + 1], p[4 * k + 2], p[4 * k + 3], dv + ((k * 2048) >> 4), (t - 1 + k) > 0);
                    wg_commit();
                }
                CLK(2);
                mbar_wait(bar_addr(sb, B_KFULL + ks), kph);
                const uint64_t dk = desc_sw128(slot_addr(sb, ks), 16);
                wg_fence();
#pragma unroll
                for (int k = 0; k < 16; k++)
                    wgmma_n64_ss(s, dp + (((k >> 2) * 16384 + (k & 3) * 32) >> 4), dk + (((k >> 2) * 8192 + (k & 3) * 32) >> 4), k > 0);
                wg_commit();
                if (w == 0) bar_arrive<2>(); else bar_arrive<3>();
                CLK(3);
                if (t > 0) {
                    wg_wait<1>();
                    if (lane == 0) release_pair(bar_addr(sb, B_VEMPTY + ((t - 1) & 1)), rank);
                }
                CLK(4);
                wg_wait<0>();
                CLK(5);
                CLKALL(t);
                if (lane == 0) release_pair(bar_addr(sb, B_KEMPTY + ks), rank);
                mbar_wait(bar_addr(sb, B_NORM + (t & 3)), (t >> 2) & 1);
                CLK(6);
                const uint32_t nb = sb + SM_NORM + (t & 3) * 256 + c * 8;
                float bias[16];
#pragma unroll
                for (int j = 0; j < 8; j++)
                    asm volatile("ld.shared.v2.f32 {%0, %1}, [%2];" : "=f"(bias[2 * j]), "=f"(bias[2 * j + 1]) : "r"(nb + j * 32) : "memory");
#pragma unroll
                for (int j = 0; j < 8; j++) {
                    const float bx = bias[2 * j], by = bias[2 * j + 1];
                    const float p00 = ex2(fmaf(s[4 * j], kC1, bx)), p01 = ex2(fmaf(s[4 * j + 1], kC1, by));
                    const float p10 = ex2(fmaf(s[4 * j + 2], kC1, bx)), p11 = ex2(fmaf(s[4 * j + 3], kC1, by));
                    ks0 += p00 + p01;
                    ks1 += p10 + p11;
                    p[2 * j] = pack_bf16(p00, p01);
                    p[2 * j + 1] = pack_bf16(p10, p11);
                }
                CLK(7);
                if (++ks == 3) { ks = 0; kph ^= 1; }
            }
            if (w == 1) bar_sync<2>(); else bar_sync<3>();
            mbar_wait(bar_addr(sb, B_VFULL + 1), 1);
            {
                const uint64_t dv = desc_sw128(slot_addr(sb, 4), 8192);
                wg_fence();
#pragma unroll
                for (int k = 0; k < 4; k++)
                    wgmma_n256_rs_tb(acc, p[4 * k], p[4 * k + 1], p[4 * k + 2], p[4 * k + 3], dv + ((k * 2048) >> 4), 1);
                wg_commit();
            }
            if (w == 0) bar_arrive<2>();
            wg_wait<0>();
            if (w == 1) bar_arrive<3>();
            PROFA(6); CLKS(11);
            ks0 += __shfl_xor_sync(0xffffffffu, ks0, 1); ks0 += __shfl_xor_sync(0xffffffffu, ks0, 2);
            ks1 += __shfl_xor_sync(0xffffffffu, ks1, 1); ks1 += __shfl_xor_sync(0xffffffffu, ks1, 2);
            if (c == 0) {
                asm volatile("st.shared.f32 [%0], %1;" :: "r"(sb + SM_KS + (w * 64 + wq * 16 + g) * 4), "f"(ks0) : "memory");
                asm volatile("st.shared.f32 [%0], %1;" :: "r"(sb + SM_KS + (w * 64 + wq * 16 + g + 8) * 4), "f"(ks1) : "memory");
            }
            uint32_t pk[64];
#pragma unroll
            for (int t = 0; t < 8; t++)
#pragma unroll
                for (int i = 0; i < 2; i++)
#pragma unroll
                    for (int jj = 0; jj < 4; jj++)
                        pk[8 * t + 4 * i + jj] = pack_bf16(acc[16 * t + 4 * jj + 2 * i], acc[16 * t + 4 * jj + 2 * i + 1]);
            auto stage = [&](int slot) {
                const uint32_t stg = slot_addr(sb, slot) + (wq * 16 + g) * 128;
                const bool odd = g & 1;
                const uint32_t o0 = (((odd ? 4 : 0) + c) ^ g) << 4, o1 = (((odd ? 0 : 4) + c) ^ g) << 4;
#pragma unroll
                for (int u = 0; u < 4; u++)
#pragma unroll
                    for (int i = 0; i < 2; i++) {
                        const uint32_t* e = pk + 16 * u + 4 * i;
                        asm volatile("st.shared.v4.u32 [%0], {%1, %2, %3, %4};" :: "r"(stg + u * 8192 + i * 1024 + o0),
                                     "r"(odd ? e[8] : e[0]), "r"(odd ? e[9] : e[1]), "r"(odd ? e[10] : e[2]), "r"(odd ? e[11] : e[3]) : "memory");
                        asm volatile("st.shared.v4.u32 [%0], {%1, %2, %3, %4};" :: "r"(stg + u * 8192 + i * 1024 + o1),
                                     "r"(odd ? e[0] : e[8]), "r"(odd ? e[1] : e[9]), "r"(odd ? e[2] : e[10]), "r"(odd ? e[3] : e[11]) : "memory");
                    }
                asm volatile("fence.proxy.async.shared::cta;" ::: "memory");
                __syncwarp();
                if (lane == 0) mbar_arrive(bar_addr(sb, B_STG + w));
            };
            auto load_a = [&]() {
                mbar_wait(bar_addr(sb, w == 0 ? B_KFULL + 2 : B_KFULL + 1), w);
                PROFW(8); CLKS(13);
                load_q_frags(f, qb0, qb1, slot_addr(sb, w == 0 ? 2 : 1), wq, lane);
                CLKG4(11);
                asm volatile("fence.proxy.async.shared::cta;" ::: "memory");
                CLKG4(10);
                __syncwarp();
                if (lane == 0) mbar_arrive(bar_addr(sb, B_ACONS + w));
            };
            if (w == 0) {
                bar_sync<3>();
                stage(4);
                PROFW(7); CLKS(12);
                load_a();
            } else {
                load_a();
                mbar_wait(bar_addr(sb, B_SFREE + 0), 0);
                stage(4);
                PROFW(7); CLKS(12);
            }
            PROFW(9); CLKS(14);
        }

        uint32_t phi[64], phib[64];
        const uint32_t qsb = slot_addr(sb, w == 0 ? 2 : 1);
        {
            const uint32_t p0 = sb + SM_P0, po01 = slot_addr(sb, 3), po23 = slot_addr(sb, 0);
            float a[64];
            gemm3(a, f, p0, p0 + 32768);
            PROFW(10); CLKS(15);
            wg_wait<0>();
            PROFW(11); CLKS(16);
            exp_to_regs<0>(phi, a, qb0, qb1);
            PROFW(12); CLKS(17);
            mbar_wait(bar_addr(sb, B_PO01), 0);
            mbar_wait(bar_addr(sb, B_PO23), 0);
            PROFW(13); CLKS(18);
            gemm3(a, f, po01, po23);
            PROFW(14); CLKS(19);
            wg_wait<0>();
            PROFW(16); CLKS(20);
            exp_to_regs<32>(phi, a, qb0, qb1);
            mbar_wait(bar_addr(sb, w == 0 ? B_KFULL + 2 : B_KFULL + 1), w ^ 1);
            PROFW(17); CLKS(21);
            load_q_frags(f, qb0, qb1, qsb, wq, lane);
            PROFW(18); CLKS(22);
            gemm3(a, f, p0, p0 + 32768);
            wg_wait<0>();
            PROFW(19); CLKS(23);
            exp_to_smem<0>(qsb, a, qb0, qb1, wq, lane);
            __syncwarp();
            PROFW(20);
            gemm3(a, f, po01, po23);
            wg_wait<0>();
            PROFW(21); CLKS(24);
            if (lane == 0) { if (KV_MC) release_pair(bar_addr(sb, B_PDEAD), rank); else mbar_arrive(bar_addr(sb, B_PDEAD)); }
            {
                const int srow = wq * 16 + ((lane >> 3) & 1) * 8 + (lane & 7);
#pragma unroll
                for (int k = 0; k < 8; k++) {
                    const int chunk = 2 * k + (lane >> 4);
                    asm volatile("ldmatrix.sync.aligned.m8n8.x4.shared.b16 {%0, %1, %2, %3}, [%4];"
                                 : "=r"(phib[4 * k]), "=r"(phib[4 * k + 1]), "=r"(phib[4 * k + 2]), "=r"(phib[4 * k + 3])
                                 : "r"(qsb + srow * 128 + (chunk >> 3) * 8192 + (((chunk & 7) ^ (srow & 7)) << 4)) : "memory");
                }
            }
            exp_to_regs<32>(phib, a, qb0, qb1);
            PROFW(22); CLKS(25);
        }
        asm volatile("barrier.cluster.arrive.relaxed.aligned;" ::: "memory");
        {
            const uint32_t kvb[4] = {slot_addr(sb, 4), sb + SM_P0, sb + SM_P0 + 32768, slot_addr(sb, 3)};
            const uint32_t mo = rank * 128 * 128, mx = (rank ^ 1) * 128 * 128;
            const int orow = h * kSeq + sc * 512 + rank * 256 + w * 64 + wq * 16 + g;
            __nv_bfloat16* pA = out + (size_t)orow * kDim + c * 8;
            __nv_bfloat16* pB = pA + 128 * kDim;
            float iA0, iA1, iB0, iB1;
            auto take_turn = [&](bool first) { if (w == 1) bar_sync<2>(); else if (!first) bar_sync<3>(); };
            auto give_turn = [&](bool last) { if (w == 0) bar_arrive<2>(); else if (!last) bar_arrive<3>(); };
            {
                float e[36];
                const uint32_t lbo = slot_addr(sb, 0) - slot_addr(sb, 4);
                const uint64_t d0 = desc_sw128(kvb[0] + mo, lbo), d1 = desc_sw128(kvb[0] + mx, lbo);
                mbar_wait(bar_addr(sb, B_KV + 0), 0);
                mbar_wait(bar_addr(sb, B_KSUM), 0);
                PROFA(23); CLKS(26);
                take_turn(true);
                wg_fence();
#pragma unroll
                for (int k = 0; k < 16; k++)
                    wgmma_n72_rs_tb(e, phi[4 * k], phi[4 * k + 1], phi[4 * k + 2], phi[4 * k + 3], (k < 8 ? d0 : d1) + (((k & 7) * 2048) >> 4), k > 0);
                wg_commit();
                give_turn(false);
                wg_wait<0>();
                CLKG4(8);
                iA0 = __fdividef(1.f, e[32] + 1e-6f);
                iA1 = __fdividef(1.f, e[34] + 1e-6f);
                store_out(e, iA0, iA1, pA);
                CLKG4(0);
                take_turn(false);
                wg_fence();
#pragma unroll
                for (int k = 0; k < 16; k++)
                    wgmma_n72_rs_tb(e, phib[4 * k], phib[4 * k + 1], phib[4 * k + 2], phib[4 * k + 3], (k < 8 ? d0 : d1) + (((k & 7) * 2048) >> 4), k > 0);
                wg_commit();
                give_turn(false);
                wg_wait<0>();
                CLKG4(9);
                iB0 = __fdividef(1.f, e[32] + 1e-6f);
                iB1 = __fdividef(1.f, e[34] + 1e-6f);
                store_out(e, iB0, iB1, pB);
                CLKG4(1);
            }
#pragma unroll
            for (int b = 1; b < 4; b++) {
                float o[32];
                const uint64_t d0 = desc_sw128(kvb[b] + mo, 16), d1 = desc_sw128(kvb[b] + mx, 16);
                mbar_wait(bar_addr(sb, B_KV + b), 0);
                take_turn(false);
                wg_fence();
#pragma unroll
                for (int k = 0; k < 16; k++)
                    wgmma_n64_rs_tb(o, phi[4 * k], phi[4 * k + 1], phi[4 * k + 2], phi[4 * k + 3], (k < 8 ? d0 : d1) + (((k & 7) * 2048) >> 4), k > 0);
                wg_commit();
                give_turn(false);
                wg_wait<0>();
                store_out(o, iA0, iA1, pA + b * 64);
                CLKG4(2 * b);
                take_turn(false);
                wg_fence();
#pragma unroll
                for (int k = 0; k < 16; k++)
                    wgmma_n64_rs_tb(o, phib[4 * k], phib[4 * k + 1], phib[4 * k + 2], phib[4 * k + 3], (k < 8 ? d0 : d1) + (((k & 7) * 2048) >> 4), k > 0);
                wg_commit();
                give_turn(b == 3);
                wg_wait<0>();
                store_out(o, iB0, iB1, pB + b * 64);
                CLKG4(2 * b + 1);
            }
        }
        PROFA(24);
        CLKS(27);
        asm volatile("barrier.cluster.wait.aligned;" ::: "memory");
    }
}

typedef CUresult (*EncodeTiledFn)(CUtensorMap*, CUtensorMapDataType, cuuint32_t, void*, const cuuint64_t*, const cuuint64_t*,
                                  const cuuint32_t*, const cuuint32_t*, CUtensorMapInterleave, CUtensorMapSwizzle,
                                  CUtensorMapL2promotion, CUtensorMapFloatOOBfill);

bool make_map(EncodeTiledFn enc, CUtensorMap* m, const void* base, uint64_t rows, uint32_t box_rows) {
    cuuint64_t dims[3] = {64, rows, 4};
    cuuint64_t strides[2] = {512, 128};
    cuuint32_t box[3] = {64, box_rows, 2};
    cuuint32_t es[3] = {1, 1, 1};
    return enc(m, CU_TENSOR_MAP_DATA_TYPE_BFLOAT16, 3, const_cast<void*>(base), dims, strides, box, es,
               CU_TENSOR_MAP_INTERLEAVE_NONE, CU_TENSOR_MAP_SWIZZLE_128B, CU_TENSOR_MAP_L2_PROMOTION_L2_256B,
               CU_TENSOR_MAP_FLOAT_OOB_FILL_NONE) == CUDA_SUCCESS;
}

}

extern "C" void kernel_launch(void* const* d_in, const int* in_sizes, int n_in, void* d_out, int out_size) {
    (void)in_sizes; (void)n_in; (void)out_size;
    static EncodeTiledFn enc = nullptr;
    if (!enc) {
        void* fn = nullptr;
        cudaDriverEntryPointQueryResult qr;
        if (cudaGetDriverEntryPoint("cuTensorMapEncodeTiled", &fn, cudaEnableDefault, &qr) != cudaSuccess || !fn) return;
        enc = (EncodeTiledFn)fn;
        cudaFuncSetAttribute(performer_kernel, cudaFuncAttributeMaxDynamicSharedMemorySize, SM_TOTAL);
    }
    CUtensorMap tq, tk, tv, tp;
    if (!make_map(enc, &tq, d_in[0], kHeads * kSeq, 64) || !make_map(enc, &tk, d_in[1], kHeads * kSeq, 64) ||
        !make_map(enc, &tv, d_in[2], kHeads * kSeq, 64) || !make_map(enc, &tp, d_in[3], 256, 128)) return;
    performer_kernel<<<128, 384, SM_TOTAL, cudaStreamPerThread>>>(tq, tk, tv, tp, (const uint8_t*)d_in[0], (const uint8_t*)d_in[1], (const uint8_t*)d_in[2],
                                                                    (const uint8_t*)d_in[3], (__nv_bfloat16*)d_out);
}
```

```cpp
#include <cuda_runtime.h>
#include <cuda_bf16.h>
#include <cuda.h>
#include <stdint.h>

namespace {

constexpr int kHeads = 16;
constexpr int kSeq = 2048;
constexpr int kDim = 256;

constexpr uint32_t SM_P0 = 0;
constexpr uint32_t SM_SLOT = 65536;
constexpr uint32_t SLOT_BYTES = 32768;
constexpr uint32_t SM_BAR = SM_SLOT + 5 * SLOT_BYTES;
constexpr uint32_t SM_NORM = SM_BAR + 512;
constexpr uint32_t SM_KS = SM_NORM + 1024;
constexpr uint32_t SM_TOTAL = SM_KS + 512;

#define A1_EARLY 0
constexpr int S_STG = 0, S_QA = 1, S_PO23 = 2, S_PO01 = 3, S_QB = 4;

constexpr int B_PROJ = 0;
constexpr int B_FULL = 1;
constexpr int B_EMPTY = 6;
constexpr int B_NORM = 11;
constexpr int B_KV = 15;
constexpr int B_STG = 19;
constexpr int B_ACONS = 21;
constexpr int B_PO01 = 23;
constexpr int B_PO23 = 24;
constexpr int B_ZERO = 25;
constexpr int B_SFREE = 26;
constexpr int B_PDEAD = 27;
constexpr int B_B0DEAD = 28;
constexpr int B_KSUM = 29;
constexpr int B_DUMPED = 30;
constexpr int B_P0DEAD = 31;

#define START_ORDER 7
#define DESC_OPAQUE 1
constexpr int kSpinLimit = 1 << 21;

__device__ uint4 g_kvacc[kHeads * 8192];
__device__ float g_ksum[kHeads * 256];
__device__ unsigned g_flag_zero[kHeads * 32];
__device__ unsigned g_flag_dump[kHeads * 32];
#define PROF(i) do {} while (0)
#define PROFW(i) do {} while (0)
#define PROFA(i) do {} while (0)
#define PROFS(i) do {} while (0)
#define CLK(i) do {} while (0)
#define CLKS(i) do {} while (0)
#define CLKP(i) do {} while (0)
#define CLKALL(i) do {} while (0)
#define CLKG4(i) do {} while (0)

__device__ __forceinline__ void mbar_init(uint32_t bar, uint32_t cnt) {
    asm volatile("mbarrier.init.shared::cta.b64 [%0], %1;" :: "r"(bar), "r"(cnt) : "memory");
}
__device__ __forceinline__ void mbar_expect_tx(uint32_t bar, uint32_t bytes) {
    asm volatile("mbarrier.arrive.expect_tx.shared::cta.b64 _, [%0], %1;" :: "r"(bar), "r"(bytes) : "memory");
}
__device__ __forceinline__ void mbar_arrive(uint32_t bar) {
    asm volatile("mbarrier.arrive.shared::cta.b64 _, [%0];" :: "r"(bar) : "memory");
}
__device__ __forceinline__ void mbar_arrive_n(uint32_t bar, uint32_t cta, uint32_t count) {
    asm volatile("{\n.reg .b32 ra;\nmapa.shared::cluster.u32 ra, %0, %1;\n"
                 "mbarrier.arrive.shared::cluster.b64 _, [ra], %2;\n}" :: "r"(bar), "r"(cta), "r"(count) : "memory");
}
__device__ __forceinline__ void mbar_wait(uint32_t bar, uint32_t parity) {
    uint32_t ok;
    int it = 0;
    do {
        asm volatile("{\n.reg .pred p;\nmbarrier.try_wait.parity.shared::cta.b64 p, [%1], %2;\nselp.u32 %0, 1, 0, p;\n}"
                     : "=r"(ok) : "r"(bar), "r"(parity) : "memory");
    } while (!ok && ++it < kSpinLimit);
}
__device__ __forceinline__ void tma_load(uint32_t dst, const CUtensorMap* tm, uint32_t bar, int row, int blk) {
    asm volatile("cp.async.bulk.tensor.3d.shared::cluster.global.mbarrier::complete_tx::bytes [%0], [%1, {%3, %4, %5}], [%2];"
                 :: "r"(dst), "l"(tm), "r"(bar), "r"(0), "r"(row), "r"(blk) : "memory");
}
__device__ __forceinline__ uint64_t policy_evict_first() {
    uint64_t p;
    asm volatile("createpolicy.fractional.L2::evict_first.b64 %0, 1.0;" : "=l"(p));
    return p;
}
__device__ __forceinline__ void tma_load_ef(uint32_t dst, const CUtensorMap* tm, uint32_t bar, int row, int blk, uint64_t pol) {
    asm volatile("cp.async.bulk.tensor.3d.shared::cluster.global.mbarrier::complete_tx::bytes.L2::cache_hint [%0], [%1, {%3, %4, %5}], [%2], %6;"
                 :: "r"(dst), "l"(tm), "r"(bar), "r"(0), "r"(row), "r"(blk), "l"(pol) : "memory");
}
__device__ __forceinline__ void tma_load_mc(uint32_t dst, const CUtensorMap* tm, uint32_t bar, int row, int blk, uint64_t pol) {
    asm volatile("cp.async.bulk.tensor.3d.shared::cluster.global.mbarrier::complete_tx::bytes.multicast::cluster.L2::cache_hint [%0], [%1, {%3, %4, %5}], [%2], %6, %7;"
                 :: "r"(dst), "l"(tm), "r"(bar), "r"(0), "r"(row), "r"(blk), "h"((uint16_t)3), "l"(pol) : "memory");
}
__device__ __forceinline__ void tma_prefetch(const CUtensorMap* tm, int row, int blk) {
    asm volatile("cp.async.bulk.prefetch.tensor.3d.L2.global.tile [%0, {%1, %2, %3}];"
                 :: "l"(tm), "r"(0), "r"(row), "r"(blk) : "memory");
}
__device__ __forceinline__ void bulk_load(uint32_t dst, const void* src, uint32_t bytes, uint32_t bar) {
    asm volatile("cp.async.bulk.shared::cluster.global.mbarrier::complete_tx::bytes [%0], [%1], %2, [%3];"
                 :: "r"(dst), "l"(src), "r"(bytes), "r"(bar) : "memory");
}
__device__ __forceinline__ void bulk_load_mc(uint32_t dst, const void* src, uint32_t bytes, uint32_t bar) {
    asm volatile("cp.async.bulk.shared::cluster.global.mbarrier::complete_tx::bytes.multicast::cluster [%0], [%1], %2, [%3], %4;"
                 :: "r"(dst), "l"(src), "r"(bytes), "r"(bar), "h"((uint16_t)3) : "memory");
}
__device__ __forceinline__ void bulk_push(uint32_t dst, uint32_t src, uint32_t bytes, uint32_t bar, uint32_t cta) {
    asm volatile("{\n.reg .b32 rd, rb;\nmapa.shared::cluster.u32 rd, %0, %4;\nmapa.shared::cluster.u32 rb, %3, %4;\n"
                 "cp.async.bulk.shared::cluster.shared::cta.mbarrier::complete_tx::bytes [rd], [%1], %2, [rb];\n}"
                 :: "r"(dst), "r"(src), "r"(bytes), "r"(bar), "r"(cta) : "memory");
}
__device__ __forceinline__ void wg_fence() { asm volatile("wgmma.fence.sync.aligned;" ::: "memory"); }
__device__ __forceinline__ void wg_commit() { asm volatile("wgmma.commit_group.sync.aligned;" ::: "memory"); }
template <int N> __device__ __forceinline__ void wg_wait() { asm volatile("wgmma.wait_group.sync.aligned %0;" :: "n"(N) : "memory"); }

__device__ __forceinline__ uint64_t desc_sw128(uint32_t addr, uint32_t lbo) {
    asm volatile("" : "+r"(addr));
    return (uint64_t)((addr & 0x3FFFF) >> 4) | ((uint64_t)(lbo >> 4) << 16) | ((uint64_t)(1024 >> 4) << 32) | (1ull << 62);
}
__device__ __forceinline__ uint32_t pack_bf16(float lo, float hi) {
    uint32_t r;
    asm("cvt.rn.bf16x2.f32 %0, %1, %2;" : "=r"(r) : "f"(hi), "f"(lo));
    return r;
}
__device__ __forceinline__ float ex2(float x) {
    float y;
    asm("ex2.approx.ftz.f32 %0, %1;" : "=f"(y) : "f"(x));
    return y;
}
__device__ __forceinline__ unsigned ld_relaxed_gpu(const unsigned* p) {
    unsigned v;
    asm volatile("ld.relaxed.gpu.global.u32 %0, [%1];" : "=r"(v) : "l"(p) : "memory");
    return v;
}
__device__ __forceinline__ void fence_gpu() { asm volatile("fence.acq_rel.gpu;" ::: "memory"); }
__device__ __forceinline__ void red_add_u32(unsigned* p, unsigned v) {
    asm volatile("red.relaxed.gpu.global.add.u32 [%0], %1;" :: "l"(p), "r"(v) : "memory");
}
__device__ __forceinline__ unsigned ld_acquire_gpu(const unsigned* p) {
    unsigned v;
    asm volatile("ld.acquire.gpu.global.u32 %0, [%1];" : "=r"(v) : "l"(p) : "memory");
    return v;
}
__device__ __forceinline__ void spin_flag(const unsigned* p, unsigned target) {
    int it = 0;
    while ((int)(ld_acquire_gpu(p) - target) < 0 && ++it < kSpinLimit) {}
}
template <int R> __device__ __forceinline__ void reg_alloc() { asm volatile("setmaxnreg.inc.sync.aligned.u32 %0;" :: "n"(R)); }
template <int R> __device__ __forceinline__ void reg_dealloc() { asm volatile("setmaxnreg.dec.sync.aligned.u32 %0;" :: "n"(R)); }

template <int N>
__device__ __forceinline__ void wgmma_n64_ss(float (&d)[N], uint64_t da, uint64_t db, int scale_d) {
    asm volatile("{\n.reg .pred p;\nsetp.ne.b32 p, %34, 0;\n"
        "wgmma.mma_async.sync.aligned.m64n64k16.f32.bf16.bf16 "
        "{%0, %1, %2, %3, %4, %5, %6, %7, %8, %9, %10, %11, %12, %13, %14, %15, "
        "%16, %17, %18, %19, %20, %21, %22, %23, %24, %25, %26, %27, %28, %29, %30, %31}, "
        "%32, %33, p, 1, 1, 0, 0;\n}\n"
        : "+f"(d[0]), "+f"(d[1]), "+f"(d[2]), "+f"(d[3]), "+f"(d[4]), "+f"(d[5]), "+f"(d[6]), "+f"(d[7]),
          "+f"(d[8]), "+f"(d[9]), "+f"(d[10]), "+f"(d[11]), "+f"(d[12]), "+f"(d[13]), "+f"(d[14]), "+f"(d[15]),
          "+f"(d[16]), "+f"(d[17]), "+f"(d[18]), "+f"(d[19]), "+f"(d[20]), "+f"(d[21]), "+f"(d[22]), "+f"(d[23]),
          "+f"(d[24]), "+f"(d[25]), "+f"(d[26]), "+f"(d[27]), "+f"(d[28]), "+f"(d[29]), "+f"(d[30]), "+f"(d[31])
        : "l"(da), "l"(db), "r"(scale_d));
}
template <int N>
__device__ __forceinline__ void wgmma_n64_rs_tb(float (&d)[N], uint32_t a0, uint32_t a1, uint32_t a2, uint32_t a3, uint64_t db, int scale_d) {
    asm volatile("{\n.reg .pred p;\nsetp.ne.b32 p, %37, 0;\n"
        "wgmma.mma_async.sync.aligned.m64n64k16.f32.bf16.bf16 "
        "{%0, %1, %2, %3, %4, %5, %6, %7, %8, %9, %10, %11, %12, %13, %14, %15, "
        "%16, %17, %18, %19, %20, %21, %22, %23, %24, %25, %26, %27, %28, %29, %30, %31}, "
        "{%32, %33, %34, %35}, %36, p, 1, 1, 1;\n}\n"
        : "+f"(d[0]), "+f"(d[1]), "+f"(d[2]), "+f"(d[3]), "+f"(d[4]), "+f"(d[5]), "+f"(d[6]), "+f"(d[7]),
          "+f"(d[8]), "+f"(d[9]), "+f"(d[10]), "+f"(d[11]), "+f"(d[12]), "+f"(d[13]), "+f"(d[14]), "+f"(d[15]),
          "+f"(d[16]), "+f"(d[17]), "+f"(d[18]), "+f"(d[19]), "+f"(d[20]), "+f"(d[21]), "+f"(d[22]), "+f"(d[23]),
          "+f"(d[24]), "+f"(d[25]), "+f"(d[26]), "+f"(d[27]), "+f"(d[28]), "+f"(d[29]), "+f"(d[30]), "+f"(d[31])
        : "r"(a0), "r"(a1), "r"(a2), "r"(a3), "l"(db), "r"(scale_d));
}
template <int N>
__device__ __forceinline__ void wgmma_n72_rs_tb(float (&d)[N], uint32_t a0, uint32_t a1, uint32_t a2, uint32_t a3, uint64_t db, int scale_d) {
    asm volatile("{\n.reg .pred p;\nsetp.ne.b32 p, %41, 0;\n"
        "wgmma.mma_async.sync.aligned.m64n72k16.f32.bf16.bf16 "
        "{%0, %1, %2, %3, %4, %5, %6, %7, %8, %9, %10, %11, %12, %13, %14, %15, "
        "%16, %17, %18, %19, %20, %21, %22, %23, %24, %25, %26, %27, %28, %29, %30, %31, "
        "%32, %33, %34, %35}, "
        "{%36, %37, %38, %39}, %40, p, 1, 1, 1;\n}\n"
        : "+f"(d[0]), "+f"(d[1]), "+f"(d[2]), "+f"(d[3]), "+f"(d[4]), "+f"(d[5]), "+f"(d[6]), "+f"(d[7]),
          "+f"(d[8]), "+f"(d[9]), "+f"(d[10]), "+f"(d[11]), "+f"(d[12]), "+f"(d[13]), "+f"(d[14]), "+f"(d[15]),
          "+f"(d[16]), "+f"(d[17]), "+f"(d[18]), "+f"(d[19]), "+f"(d[20]), "+f"(d[21]), "+f"(d[22]), "+f"(d[23]),
          "+f"(d[24]), "+f"(d[25]), "+f"(d[26]), "+f"(d[27]), "+f"(d[28]), "+f"(d[29]), "+f"(d[30]), "+f"(d[31]),
          "+f"(d[32]), "+f"(d[33]), "+f"(d[34]), "+f"(d[35])
        : "r"(a0), "r"(a1), "r"(a2), "r"(a3), "l"(db), "r"(scale_d));
}
template <int N>
__device__ __forceinline__ void wgmma_n128_rs(float (&d)[N], uint32_t a0, uint32_t a1, uint32_t a2, uint32_t a3, uint64_t db, int scale_d) {
    asm volatile("{\n.reg .pred p;\nsetp.ne.b32 p, %69, 0;\n"
        "wgmma.mma_async.sync.aligned.m64n128k16.f32.bf16.bf16 "
        "{%0, %1, %2, %3, %4, %5, %6, %7, %8, %9, %10, %11, %12, %13, %14, %15, "
        "%16, %17, %18, %19, %20, %21, %22, %23, %24, %25, %26, %27, %28, %29, %30, %31, "
        "%32, %33, %34, %35, %36, %37, %38, %39, %40, %41, %42, %43, %44, %45, %46, %47, "
        "%48, %49, %50, %51, %52, %53, %54, %55, %56, %57, %58, %59, %60, %61, %62, %63}, "
        "{%64, %65, %66, %67}, %68, p, 1, 1, 0;\n}\n"
        : "+f"(d[0]), "+f"(d[1]), "+f"(d[2]), "+f"(d[3]), "+f"(d[4]), "+f"(d[5]), "+f"(d[6]), "+f"(d[7]),
          "+f"(d[8]), "+f"(d[9]), "+f"(d[10]), "+f"(d[11]), "+f"(d[12]), "+f"(d[13]), "+f"(d[14]), "+f"(d[15]),
          "+f"(d[16]), "+f"(d[17]), "+f"(d[18]), "+f"(d[19]), "+f"(d[20]), "+f"(d[21]), "+f"(d[22]), "+f"(d[23]),
          "+f"(d[24]), "+f"(d[25]), "+f"(d[26]), "+f"(d[27]), "+f"(d[28]), "+f"(d[29]), "+f"(d[30]), "+f"(d[31]),
          "+f"(d[32]), "+f"(d[33]), "+f"(d[34]), "+f"(d[35]), "+f"(d[36]), "+f"(d[37]), "+f"(d[38]), "+f"(d[39]),
          "+f"(d[40]), "+f"(d[41]), "+f"(d[42]), "+f"(d[43]), "+f"(d[44]), "+f"(d[45]), "+f"(d[46]), "+f"(d[47]),
          "+f"(d[48]), "+f"(d[49]), "+f"(d[50]), "+f"(d[51]), "+f"(d[52]), "+f"(d[53]), "+f"(d[54]), "+f"(d[55]),
          "+f"(d[56]), "+f"(d[57]), "+f"(d[58]), "+f"(d[59]), "+f"(d[60]), "+f"(d[61]), "+f"(d[62]), "+f"(d[63])
        : "r"(a0), "r"(a1), "r"(a2), "r"(a3), "l"(db), "r"(scale_d));
}
template <int N>
__device__ __forceinline__ void wgmma_n128_ss(float (&d)[N], uint64_t da, uint64_t db, int scale_d) {
    asm volatile("{\n.reg .pred p;\nsetp.ne.b32 p, %66, 0;\n"
        "wgmma.mma_async.sync.aligned.m64n128k16.f32.bf16.bf16 "
        "{%0, %1, %2, %3, %4, %5, %6, %7, %8, %9, %10, %11, %12, %13, %14, %15, "
        "%16, %17, %18, %19, %20, %21, %22, %23, %24, %25, %26, %27, %28, %29, %30, %31, "
        "%32, %33, %34, %35, %36, %37, %38, %39, %40, %41, %42, %43, %44, %45, %46, %47, "
        "%48, %49, %50, %51, %52, %53, %54, %55, %56, %57, %58, %59, %60, %61, %62, %63}, "
        "%64, %65, p, 1, 1, 0, 0;\n}\n"
        : "+f"(d[0]), "+f"(d[1]), "+f"(d[2]), "+f"(d[3]), "+f"(d[4]), "+f"(d[5]), "+f"(d[6]), "+f"(d[7]),
          "+f"(d[8]), "+f"(d[9]), "+f"(d[10]), "+f"(d[11]), "+f"(d[12]), "+f"(d[13]), "+f"(d[14]), "+f"(d[15]),
          "+f"(d[16]), "+f"(d[17]), "+f"(d[18]), "+f"(d[19]), "+f"(d[20]), "+f"(d[21]), "+f"(d[22]), "+f"(d[23]),
          "+f"(d[24]), "+f"(d[25]), "+f"(d[26]), "+f"(d[27]), "+f"(d[28]), "+f"(d[29]), "+f"(d[30]), "+f"(d[31]),
          "+f"(d[32]), "+f"(d[33]), "+f"(d[34]), "+f"(d[35]), "+f"(d[36]), "+f"(d[37]), "+f"(d[38]), "+f"(d[39]),
          "+f"(d[40]), "+f"(d[41]), "+f"(d[42]), "+f"(d[43]), "+f"(d[44]), "+f"(d[45]), "+f"(d[46]), "+f"(d[47]),
          "+f"(d[48]), "+f"(d[49]), "+f"(d[50]), "+f"(d[51]), "+f"(d[52]), "+f"(d[53]), "+f"(d[54]), "+f"(d[55]),
          "+f"(d[56]), "+f"(d[57]), "+f"(d[58]), "+f"(d[59]), "+f"(d[60]), "+f"(d[61]), "+f"(d[62]), "+f"(d[63])
        : "l"(da), "l"(db), "r"(scale_d));
}
template <int N>
__device__ __forceinline__ void wgmma_n256_rs_tb(float (&d)[N], uint32_t a0, uint32_t a1, uint32_t a2, uint32_t a3, uint64_t db, int scale_d) {
    asm volatile("{\n.reg .pred p;\nsetp.ne.b32 p, %133, 0;\n"
        "wgmma.mma_async.sync.aligned.m64n256k16.f32.bf16.bf16 "
        "{%0, %1, %2, %3, %4, %5, %6, %7, %8, %9, %10, %11, %12, %13, %14, %15, "
        "%16, %17, %18, %19, %20, %21, %22, %23, %24, %25, %26, %27, %28, %29, %30, %31, "
        "%32, %33, %34, %35, %36, %37, %38, %39, %40, %41, %42, %43, %44, %45, %46, %47, "
        "%48, %49, %50, %51, %52, %53, %54, %55, %56, %57, %58, %59, %60, %61, %62, %63, "
        "%64, %65, %66, %67, %68, %69, %70, %71, %72, %73, %74, %75, %76, %77, %78, %79, "
        "%80, %81, %82, %83, %84, %85, %86, %87, %88, %89, %90, %91, %92, %93, %94, %95, "
        "%96, %97, %98, %99, %100, %101, %102, %103, %104, %105, %106, %107, %108, %109, %110, %111, "
        "%112, %113, %114, %115, %116, %117, %118, %119, %120, %121, %122, %123, %124, %125, %126, %127}, "
        "{%128, %129, %130, %131}, %132, p, 1, 1, 1;\n}\n"
        : "+f"(d[0]), "+f"(d[1]), "+f"(d[2]), "+f"(d[3]), "+f"(d[4]), "+f"(d[5]), "+f"(d[6]), "+f"(d[7]),
          "+f"(d[8]), "+f"(d[9]), "+f"(d[10]), "+f"(d[11]), "+f"(d[12]), "+f"(d[13]), "+f"(d[14]), "+f"(d[15]),
          "+f"(d[16]), "+f"(d[17]), "+f"(d[18]), "+f"(d[19]), "+f"(d[20]), "+f"(d[21]), "+f"(d[22]), "+f"(d[23]),
          "+f"(d[24]), "+f"(d[25]), "+f"(d[26]), "+f"(d[27]), "+f"(d[28]), "+f"(d[29]), "+f"(d[30]), "+f"(d[31]),
          "+f"(d[32]), "+f"(d[33]), "+f"(d[34]), "+f"(d[35]), "+f"(d[36]), "+f"(d[37]), "+f"(d[38]), "+f"(d[39]),
          "+f"(d[40]), "+f"(d[41]), "+f"(d[42]), "+f"(d[43]), "+f"(d[44]), "+f"(d[45]), "+f"(d[46]), "+f"(d[47]),
          "+f"(d[48]), "+f"(d[49]), "+f"(d[50]), "+f"(d[51]), "+f"(d[52]), "+f"(d[53]), "+f"(d[54]), "+f"(d[55]),
          "+f"(d[56]), "+f"(d[57]), "+f"(d[58]), "+f"(d[59]), "+f"(d[60]), "+f"(d[61]), "+f"(d[62]), "+f"(d[63]),
          "+f"(d[64]), "+f"(d[65]), "+f"(d[66]), "+f"(d[67]), "+f"(d[68]), "+f"(d[69]), "+f"(d[70]), "+f"(d[71]),
          "+f"(d[72]), "+f"(d[73]), "+f"(d[74]), "+f"(d[75]), "+f"(d[76]), "+f"(d[77]), "+f"(d[78]), "+f"(d[79]),
          "+f"(d[80]), "+f"(d[81]), "+f"(d[82]), "+f"(d[83]), "+f"(d[84]), "+f"(d[85]), "+f"(d[86]), "+f"(d[87]),
          "+f"(d[88]), "+f"(d[89]), "+f"(d[90]), "+f"(d[91]), "+f"(d[92]), "+f"(d[93]), "+f"(d[94]), "+f"(d[95]),
          "+f"(d[96]), "+f"(d[97]), "+f"(d[98]), "+f"(d[99]), "+f"(d[100]), "+f"(d[101]), "+f"(d[102]), "+f"(d[103]),
          "+f"(d[104]), "+f"(d[105]), "+f"(d[106]), "+f"(d[107]), "+f"(d[108]), "+f"(d[109]), "+f"(d[110]), "+f"(d[111]),
          "+f"(d[112]), "+f"(d[113]), "+f"(d[114]), "+f"(d[115]), "+f"(d[116]), "+f"(d[117]), "+f"(d[118]), "+f"(d[119]),
          "+f"(d[120]), "+f"(d[121]), "+f"(d[122]), "+f"(d[123]), "+f"(d[124]), "+f"(d[125]), "+f"(d[126]), "+f"(d[127])
        : "r"(a0), "r"(a1), "r"(a2), "r"(a3), "l"(db), "r"(scale_d));
}

constexpr float kC1 = 0.25f * 1.4426950408889634f;
constexpr float kC2 = -1.4426950408889634f / 32.0f;
constexpr float kC3 = -4.0f;

__device__ __forceinline__ uint32_t slot_addr(uint32_t sb, int s) { return sb + SM_SLOT + s * SLOT_BYTES; }
__device__ __forceinline__ uint32_t bar_addr(uint32_t sb, int b) { return sb + SM_BAR + b * 8; }

__device__ __forceinline__ void release_pair(uint32_t bar, uint32_t rank, uint32_t count = 1) {
    mbar_arrive_n(bar, rank, count);
    mbar_arrive_n(bar, rank ^ 1, count);
}

__device__ __forceinline__ float row_bias(uint32_t tile, int row, int half) {
    const uint32_t base = tile + half * 16384 + row * 128;
    const uint32_t sw = ((row & 7) ^ (half << 2)) << 4;
    float s0 = 0.f, s1 = 0.f, s2 = 0.f, s3 = 0.f;
#pragma unroll
    for (int bt = 0; bt < 4; bt++) {
        uint32_t x[4][4];
#pragma unroll
        for (int i = 0; i < 4; i++)
            asm volatile("ld.shared.v4.u32 {%0, %1, %2, %3}, [%4];" : "=r"(x[i][0]), "=r"(x[i][1]), "=r"(x[i][2]), "=r"(x[i][3])
                         : "r"(base + (bt >> 1) * 8192 + ((((bt & 1) * 4 + i) << 4) ^ sw)));
#pragma unroll
        for (int i = 0; i < 4; i++) {
            float a;
            a = __uint_as_float(x[i][0] << 16); s0 = fmaf(a, a, s0);
            a = __uint_as_float(x[i][0] & 0xffff0000u); s1 = fmaf(a, a, s1);
            a = __uint_as_float(x[i][1] << 16); s2 = fmaf(a, a, s2);
            a = __uint_as_float(x[i][1] & 0xffff0000u); s3 = fmaf(a, a, s3);
            a = __uint_as_float(x[i][2] << 16); s0 = fmaf(a, a, s0);
            a = __uint_as_float(x[i][2] & 0xffff0000u); s1 = fmaf(a, a, s1);
            a = __uint_as_float(x[i][3] << 16); s2 = fmaf(a, a, s2);
            a = __uint_as_float(x[i][3] & 0xffff0000u); s3 = fmaf(a, a, s3);
        }
    }
    float s = (s0 + s1) + (s2 + s3);
    s += __shfl_xor_sync(0xffffffffu, s, 1);
    return fmaf(s, kC2, kC3);
}
__device__ __forceinline__ void st_async_f32(uint32_t addr, float v, uint32_t bar, uint32_t cta) {
    asm volatile("{\n.reg .b32 ra, rb;\nmapa.shared::cluster.u32 ra, %0, %3;\nmapa.shared::cluster.u32 rb, %2, %3;\n"
                 "st.async.weak.shared::cluster.mbarrier::complete_tx::bytes.f32 [ra], %1, [rb];\n}"
                 :: "r"(addr), "f"(v), "r"(bar), "r"(cta) : "memory");
}

__device__ __forceinline__ void load_q_frags(uint32_t (&f)[64], float& qb0, float& qb1, uint32_t tile, int wq, int lane) {
    const int row = wq * 16 + (lane & 7) + ((lane >> 3) & 1) * 8;
    const uint32_t base = tile + row * 128;
#pragma unroll
    for (int k = 0; k < 16; k++) {
        const int chunk = 2 * k + (lane >> 4);
        asm volatile("ldmatrix.sync.aligned.m8n8.x4.shared.b16 {%0, %1, %2, %3}, [%4];"
                     : "=r"(f[4 * k]), "=r"(f[4 * k + 1]), "=r"(f[4 * k + 2]), "=r"(f[4 * k + 3])
                     : "r"(base + (k >> 2) * 8192 + (((chunk & 7) ^ (row & 7)) << 4)));
    }
    float s0 = 0.f, s1 = 0.f, s2 = 0.f, s3 = 0.f;
#pragma unroll
    for (int k = 0; k < 32; k++) {
        float a;
        a = __uint_as_float(f[2 * k] << 16); s0 = fmaf(a, a, s0);
        a = __uint_as_float(f[2 * k] & 0xffff0000u); s1 = fmaf(a, a, s1);
        a = __uint_as_float(f[2 * k + 1] << 16); s2 = fmaf(a, a, s2);
        a = __uint_as_float(f[2 * k + 1] & 0xffff0000u); s3 = fmaf(a, a, s3);
    }
    s0 += s1; s2 += s3;
    s0 += __shfl_xor_sync(0xffffffffu, s0, 1); s2 += __shfl_xor_sync(0xffffffffu, s2, 1);
    s0 += __shfl_xor_sync(0xffffffffu, s0, 2); s2 += __shfl_xor_sync(0xffffffffu, s2, 2);
    qb0 = fmaf(s0, kC2, kC3);
    qb1 = fmaf(s2, kC2, kC3);
}
__device__ __forceinline__ void gemm3(float (&d)[64], const uint32_t (&f)[64], uint32_t b01, uint32_t b23) {
    const uint64_t d0 = desc_sw128(b01, 16), d1 = desc_sw128(b23, 16);
    wg_fence();
#pragma unroll
    for (int k = 0; k < 16; k++)
        wgmma_n128_rs(d, f[4 * k], f[4 * k + 1], f[4 * k + 2], f[4 * k + 3],
                      (k < 8 ? d0 : d1) + ((((k >> 2) & 1) * 16384 + (k & 3) * 32) >> 4), k > 0);
    wg_commit();
}
template <int K0>
__device__ __forceinline__ void gemm3_ss(float (&d)[64], uint32_t qs, uint32_t pb) {
    const uint64_t da = desc_sw128(qs + (K0 >> 2) * 8192, 16), db = desc_sw128(pb, 16);
#pragma unroll
    for (int k = 0; k < 8; k++)
        wgmma_n128_ss(d, da + (((k >> 2) * 8192 + (k & 3) * 32) >> 4), db + (((k >> 2) * 16384 + (k & 3) * 32) >> 4), (K0 + k) > 0);
}
template <int K0>
__device__ __forceinline__ void tile_sumsq(float& s0, float& s1, uint32_t tile, int wq, int lane) {
    const int row = wq * 16 + (lane & 7) + ((lane >> 3) & 1) * 8;
    const uint32_t base = tile + row * 128;
    float t0 = 0.f, t1 = 0.f;
#pragma unroll
    for (int kb = 0; kb < 2; kb++) {
        uint32_t x[4][4];
#pragma unroll
        for (int i = 0; i < 4; i++) {
            const int k = K0 + kb * 4 + i, chunk = 2 * k + (lane >> 4);
            asm volatile("ldmatrix.sync.aligned.m8n8.x4.shared.b16 {%0, %1, %2, %3}, [%4];"
                         : "=r"(x[i][0]), "=r"(x[i][1]), "=r"(x[i][2]), "=r"(x[i][3])
                         : "r"(base + (k >> 2) * 8192 + (((chunk & 7) ^ (row & 7)) << 4)));
        }
#pragma unroll
        for (int i = 0; i < 4; i++) {
            float a;
            a = __uint_as_float(x[i][0] << 16); s0 = fmaf(a, a, s0);
            a = __uint_as_float(x[i][0] & 0xffff0000u); t0 = fmaf(a, a, t0);
            a = __uint_as_float(x[i][1] << 16); s1 = fmaf(a, a, s1);
            a = __uint_as_float(x[i][1] & 0xffff0000u); t1 = fmaf(a, a, t1);
            a = __uint_as_float(x[i][2] << 16); s0 = fmaf(a, a, s0);
            a = __uint_as_float(x[i][2] & 0xffff0000u); t0 = fmaf(a, a, t0);
            a = __uint_as_float(x[i][3] << 16); s1 = fmaf(a, a, s1);
            a = __uint_as_float(x[i][3] & 0xffff0000u); t1 = fmaf(a, a, t1);
        }
    }
    s0 += t0;
    s1 += t1;
}
template <int O>
__device__ __forceinline__ void exp_to_regs(uint32_t (&phi)[64], const float (&a)[64], float qb0, float qb1) {
#pragma unroll
    for (int j = 0; j < 16; j++) {
        phi[O + 2 * j] = pack_bf16(ex2(fmaf(a[4 * j], kC1, qb0)), ex2(fmaf(a[4 * j + 1], kC1, qb0)));
        phi[O + 2 * j + 1] = pack_bf16(ex2(fmaf(a[4 * j + 2], kC1, qb1)), ex2(fmaf(a[4 * j + 3], kC1, qb1)));
    }
}
template <int ID> __device__ __forceinline__ void bar_sync() { asm volatile("bar.sync %0, 256;" :: "n"(ID) : "memory"); }
template <int ID> __device__ __forceinline__ void bar_arrive() { asm volatile("bar.arrive %0, 256;" :: "n"(ID) : "memory"); }

template <int N>
__device__ __forceinline__ void store_out(const float (&o)[N], float inv0, float inv1, __nv_bfloat16* p0) {
#pragma unroll
    for (int t = 0; t < 2; t++) {
#pragma unroll
        for (int i = 0; i < 2; i++) {
            const float inv = i ? inv1 : inv0;
            uint4 v;
            v.x = pack_bf16(o[16 * t + 2 * i] * inv, o[16 * t + 2 * i + 1] * inv);
            v.y = pack_bf16(o[16 * t + 4 + 2 * i] * inv, o[16 * t + 4 + 2 * i + 1] * inv);
            v.z = pack_bf16(o[16 * t + 8 + 2 * i] * inv, o[16 * t + 8 + 2 * i + 1] * inv);
            v.w = pack_bf16(o[16 * t + 12 + 2 * i] * inv, o[16 * t + 12 + 2 * i + 1] * inv);
            *reinterpret_cast<uint4*>(p0 + i * 8 * kDim + t * 32) = v;
        }
    }
}

__global__ void __cluster_dims__(2, 1, 1) __launch_bounds__(384, 1)
performer_kernel(const __grid_constant__ CUtensorMap tm_q, const __grid_constant__ CUtensorMap tm_k,
                 const __grid_constant__ CUtensorMap tm_v, const __grid_constant__ CUtensorMap tm_p,
                 const uint8_t* __restrict__ kptr, const uint8_t* __restrict__ pptr, __nv_bfloat16* __restrict__ out) {
    extern __shared__ __align__(1024) uint8_t smem[];
    const uint32_t sb = (uint32_t)__cvta_generic_to_shared(smem);
    const int tid = threadIdx.x, lane = tid & 31;
    const int warp = __shfl_sync(0xffffffffu, tid >> 5, 0);
    uint32_t rank;
    asm volatile("mov.u32 %0, %%cluster_ctarank;" : "=r"(rank));
    const int cta = blockIdx.x, pair = cta >> 1, h = pair >> 2, sc = pair & 3;

    if (tid == 64) {
        asm volatile("cp.async.bulk.prefetch.L2.global [%0], %1;"
                     :: "l"(kptr + (size_t)(h * kSeq + sc * 512 + rank * 32) * 512), "r"(16384) : "memory");
        asm volatile("cp.async.bulk.prefetch.L2.global [%0], %1;" :: "l"(pptr + cta * 1024), "r"(1024) : "memory");
    }
    if (tid == 32) {
        asm volatile("prefetch.tensormap [%0];" :: "l"(&tm_k) : "memory");
        asm volatile("prefetch.tensormap [%0];" :: "l"(&tm_p) : "memory");
        asm volatile("prefetch.tensormap [%0];" :: "l"(&tm_v) : "memory");
        asm volatile("prefetch.tensormap [%0];" :: "l"(&tm_q) : "memory");
    }
    if (tid == 0) {
        PROF(0);
        mbar_init(bar_addr(sb, B_PROJ), 1);
#pragma unroll
        for (int i = 0; i < 5; i++) { mbar_init(bar_addr(sb, B_FULL + i), 1); mbar_init(bar_addr(sb, B_EMPTY + i), 20); }
#pragma unroll
        for (int i = 0; i < 4; i++) { mbar_init(bar_addr(sb, B_KV + i), 1); mbar_init(bar_addr(sb, B_NORM + i), 1); }
#pragma unroll
        for (int i = 0; i < 2; i++) { mbar_init(bar_addr(sb, B_STG + i), 4); mbar_init(bar_addr(sb, B_ACONS + i), 4); }
        mbar_init(bar_addr(sb, B_PO01), 1);
        mbar_init(bar_addr(sb, B_PO23), 1);
        mbar_init(bar_addr(sb, B_ZERO), 1);
        mbar_init(bar_addr(sb, B_SFREE), 1);
        mbar_init(bar_addr(sb, B_PDEAD), 8);
        mbar_init(bar_addr(sb, B_P0DEAD), 8);
        mbar_init(bar_addr(sb, B_B0DEAD), 4);
        mbar_init(bar_addr(sb, B_KSUM), 1);
        mbar_init(bar_addr(sb, B_DUMPED), 1);
        asm volatile("fence.mbarrier_init.release.cluster;" ::: "memory");
    }
    __syncwarp();
    asm volatile("barrier.cluster.arrive.relaxed.aligned;" ::: "memory");
    asm volatile("barrier.cluster.wait.aligned;" ::: "memory");

    if (warp < 4) {
        reg_dealloc<40>();
        if (warp == 0) {
            if (lane == 0) {
                const int row0 = h * kSeq + sc * 512;
                const uint64_t pol = policy_evict_first();
                auto load_item = [&](int i) {
                    const int s = i % 5;
                    if (i >= 5) mbar_wait(bar_addr(sb, B_EMPTY + s), (i / 5 - 1) & 1);
                    mbar_expect_tx(bar_addr(sb, B_FULL + s), SLOT_BYTES);
                    tma_load_mc(slot_addr(sb, s) + rank * 16384, (i & 1) ? &tm_v : &tm_k, bar_addr(sb, B_FULL + s),
                                row0 + (i >> 1) * 64, rank * 2, pol);
                };
                PROFS(1);
                load_item(0);
                mbar_expect_tx(bar_addr(sb, B_PROJ), 65536);
                tma_load(sb + SM_P0, &tm_p, bar_addr(sb, B_PROJ), rank * 128, 0);
                tma_load(sb + SM_P0 + 32768, &tm_p, bar_addr(sb, B_PROJ), rank * 128, 2);
                load_item(1);
                load_item(2);
                mbar_wait(bar_addr(sb, B_FULL + 0), 0);
                PROFS(3);
                load_item(3);
                mbar_wait(bar_addr(sb, B_FULL + 1), 0);
                load_item(4);
#pragma unroll 1
                for (int i = 5; i < 16; i++) load_item(i);
                CLKP(0);
                const int qrow = row0 + rank * 256;
                auto load_q = [&](int piece, int slot) {
                    mbar_expect_tx(bar_addr(sb, B_FULL + slot), SLOT_BYTES);
                    tma_load_ef(slot_addr(sb, slot), &tm_q, bar_addr(sb, B_FULL + slot), qrow + piece * 64, 0, pol);
                    tma_load_ef(slot_addr(sb, slot) + 16384, &tm_q, bar_addr(sb, B_FULL + slot), qrow + piece * 64, 2, pol);
                };
                mbar_wait(bar_addr(sb, B_EMPTY + 1), 0);
                load_q(0, S_QA);
                mbar_wait(bar_addr(sb, B_EMPTY + 2), 0);
                mbar_expect_tx(bar_addr(sb, B_PO23), SLOT_BYTES);
                tma_load(slot_addr(sb, S_PO23), &tm_p, bar_addr(sb, B_PO23), (rank ^ 1) * 128, 2);
                CLKP(1);
                mbar_wait(bar_addr(sb, B_EMPTY + 3), 0);
                CLKP(3);
                mbar_expect_tx(bar_addr(sb, B_PO01), SLOT_BYTES);
                tma_load(slot_addr(sb, S_PO01), &tm_p, bar_addr(sb, B_PO01), (rank ^ 1) * 128, 0);
                mbar_wait(bar_addr(sb, B_EMPTY + 4), 0);
                load_q(1, S_QB);
                CLKP(4);
                mbar_wait(bar_addr(sb, B_ACONS + 0), 0);
                load_q(2, S_QA);
                CLKP(7);
                mbar_wait(bar_addr(sb, B_ACONS + 1), 0);
                load_q(3, S_QB);
                CLKP(8);
            }
            __syncwarp();
        } else if (warp < 3) {
            const int w = warp - 1;
            const int row = rank * 32 + w * 16 + (lane >> 1);
            int s = 0, ph = 0;
#pragma unroll 1
            for (int t = 0; t < 8; t++) {
                const uint32_t nbar = bar_addr(sb, B_NORM + (t & 3));
                if (w == 0 && lane == 0) mbar_expect_tx(nbar, 256);
                mbar_wait(bar_addr(sb, B_FULL + s), ph);
                const float b = row_bias(slot_addr(sb, s), row, lane & 1);
                if (!(lane & 1)) {
                    const uint32_t dst = sb + SM_NORM + (t & 3) * 256 + row * 4;
                    st_async_f32(dst, b, nbar, 0);
                    st_async_f32(dst, b, nbar, 1);
                }
                __syncwarp();
                if (lane == 0) release_pair(bar_addr(sb, B_EMPTY + s), rank);
                s += 2;
                if (s >= 5) { s -= 5; ph ^= 1; }
            }
            if (w == 0 && lane == 0) {
                const uint32_t src = slot_addr(sb, S_STG);
                mbar_wait(bar_addr(sb, B_ZERO), 0);
#pragma unroll 1
                for (int g2 = 0; g2 < 2; g2++) {
                    uint8_t* dst = reinterpret_cast<uint8_t*>(g_kvacc + h * 8192) + (rank * 128 + g2 * 64) * 128;
                    mbar_wait(bar_addr(sb, B_STG + g2), 0);
                    CLKP(17 + g2);
                    asm volatile("fence.proxy.async.global;" ::: "memory");
                    asm volatile("cp.reduce.async.bulk.global.shared::cta.bulk_group.add.f32 [%0], [%1], %2;"
                                 :: "l"(g_ksum + h * 256 + rank * 128 + g2 * 64), "r"(sb + SM_KS + g2 * 256), "r"(256) : "memory");
#pragma unroll 1
                    for (int b = 0; b < 8; b++) {
                        asm volatile("cp.reduce.async.bulk.global.shared::cta.bulk_group.add.noftz.bf16 [%0], [%1], %2;"
                                     :: "l"(dst + (b >> 1) * 32768 + (b & 1) * 4096), "r"(src + b * 4096), "r"(4096) : "memory");
                        asm volatile("cp.async.bulk.commit_group;" ::: "memory");
                        asm volatile("cp.async.bulk.wait_group.read 0;" ::: "memory");
                    }
                    if (g2 == 0) mbar_arrive(bar_addr(sb, B_SFREE));
                    CLKP(9 + g2);
                }
                asm volatile("cp.async.bulk.wait_group 0;" ::: "memory");
                CLKP(12);
                asm volatile("fence.proxy.async.global;" ::: "memory");
                red_add_u32(&g_flag_dump[h * 32], 1);
                CLKP(14);
                mbar_arrive(bar_addr(sb, B_DUMPED));
            }
            __syncwarp();
        } else {
            unsigned target = 0;
            if (lane == 0) target = ld_relaxed_gpu(&g_flag_dump[h * 32]) + 8;
            mbar_wait(bar_addr(sb, B_NORM + 1), 0);
            uint4* z = g_kvacc + h * 8192 + (cta & 7) * 1024;
#pragma unroll 4
            for (int i = 0; i < 32; i++) z[i * 32 + lane] = make_uint4(0, 0, 0, 0);
            g_ksum[h * 256 + (cta & 7) * 32 + lane] = 0.f;
            __syncwarp();
            if (lane == 0) {
                fence_gpu();
                red_add_u32(&g_flag_zero[h * 32], 1);
                spin_flag(&g_flag_zero[h * 32], target);
                asm volatile("fence.proxy.async.global;" ::: "memory");
                mbar_arrive(bar_addr(sb, B_ZERO));
                mbar_wait(bar_addr(sb, B_DUMPED), 0);
                spin_flag(&g_flag_dump[h * 32], target);
                asm volatile("fence.proxy.async.global;" ::: "memory");
                CLKP(15);
                mbar_expect_tx(bar_addr(sb, B_KV + 0), SLOT_BYTES);
                bulk_load(slot_addr(sb, S_STG), g_kvacc + h * 8192, SLOT_BYTES, bar_addr(sb, B_KV + 0));
            }
            __syncwarp();
            uint32_t kb[8];
#pragma unroll
            for (int i = 0; i < 8; i++) {
                const float v = __ldcg(g_ksum + h * 256 + i * 32 + lane);
                kb[i] = pack_bf16(v, v);
            }
            const uint8_t* kvsrc = reinterpret_cast<const uint8_t*>(g_kvacc + h * 8192);
            if (lane == 0) {
                mbar_wait(bar_addr(sb, B_P0DEAD), 0);
                mbar_expect_tx(bar_addr(sb, B_KV + 1), SLOT_BYTES);
                bulk_load(sb + SM_P0, kvsrc + 32768, SLOT_BYTES, bar_addr(sb, B_KV + 1));
            }
            mbar_wait(bar_addr(sb, B_B0DEAD), 0);
#pragma unroll
            for (int i = 0; i < 8; i++) {
                const int m = i * 32 + lane;
                asm volatile("st.shared.v4.u32 [%0], {%1, %1, %1, %1};" :: "r"(slot_addr(sb, S_QA) + m * 128 + ((m & 7) << 4)), "r"(kb[i]) : "memory");
            }
            asm volatile("fence.proxy.async.shared::cta;" ::: "memory");
            __syncwarp();
            if (lane == 0) {
                mbar_arrive(bar_addr(sb, B_KSUM));
                CLKP(16);
                mbar_wait(bar_addr(sb, B_KV + 1), 0);
                mbar_expect_tx(bar_addr(sb, B_KV + 2), SLOT_BYTES);
                bulk_load(sb + SM_P0 + 32768, kvsrc + 65536, SLOT_BYTES, bar_addr(sb, B_KV + 2));
                mbar_wait(bar_addr(sb, B_PDEAD), 0);
                mbar_expect_tx(bar_addr(sb, B_KV + 3), SLOT_BYTES);
                bulk_load(slot_addr(sb, S_PO01), kvsrc + 98304, SLOT_BYTES, bar_addr(sb, B_KV + 3));
            }
            __syncwarp();
        }
        asm volatile("barrier.cluster.arrive.relaxed.aligned;" ::: "memory");
        asm volatile("barrier.cluster.wait.aligned;" ::: "memory");
    } else {
        reg_alloc<232>();
        const int w = (warp - 4) >> 2, wq = warp & 3, g = lane >> 2, c = lane & 3;
        float ks0 = 0.f, ks1 = 0.f, qb0, qb1;
        uint32_t f[64], pk[64];
        auto stage = [&](int slot) {
            const uint32_t stg = slot_addr(sb, slot) + (wq * 16 + g) * 128;
            const bool odd = g & 1;
            const uint32_t o0 = (((odd ? 4 : 0) + c) ^ g) << 4, o1 = (((odd ? 0 : 4) + c) ^ g) << 4;
#pragma unroll
            for (int u = 0; u < 4; u++)
#pragma unroll
                for (int i = 0; i < 2; i++) {
                    const uint32_t* e = pk + 16 * u + 4 * i;
                    asm volatile("st.shared.v4.u32 [%0], {%1, %2, %3, %4};" :: "r"(stg + u * 8192 + i * 1024 + o0),
                                 "r"(odd ? e[8] : e[0]), "r"(odd ? e[9] : e[1]), "r"(odd ? e[10] : e[2]), "r"(odd ? e[11] : e[3]) : "memory");
                    asm volatile("st.shared.v4.u32 [%0], {%1, %2, %3, %4};" :: "r"(stg + u * 8192 + i * 1024 + o1),
                                 "r"(odd ? e[0] : e[8]), "r"(odd ? e[1] : e[9]), "r"(odd ? e[2] : e[10]), "r"(odd ? e[3] : e[11]) : "memory");
                }
            asm volatile("fence.proxy.async.shared::cta;" ::: "memory");
            __syncwarp();
            if (lane == 0) mbar_arrive(bar_addr(sb, B_STG + w));
        };
        {
            float acc[128];
            uint32_t p[16];
            const uint64_t dp = desc_sw128(sb + SM_P0 + w * 8192, 16);
            mbar_wait(bar_addr(sb, B_PROJ), 0);
            PROFA(0); CLKS(28);
            int ks = 0, kph = 0;
#pragma unroll 1
            for (int t = 0; t < 8; t++) {
                float s[32];
                const int vs = ks == 0 ? 4 : ks - 1, vph = ks == 0 ? kph ^ 1 : kph;
                CLK(0);
                if (w == 1) bar_sync<2>(); else if (t > 0) bar_sync<3>();
                CLK(1);
                if (t > 0) {
                    mbar_wait(bar_addr(sb, B_FULL + vs), vph);
                    const uint64_t dv = desc_sw128(slot_addr(sb, vs), 8192);
                    wg_fence();
#pragma unroll
                    for (int k = 0; k < 4; k++)
                        wgmma_n256_rs_tb(acc, p[4 * k], p[4 * k + 1], p[4 * k + 2], p[4 * k + 3], dv + ((k * 2048) >> 4), (t - 1 + k) > 0);
                    wg_commit();
                }
                CLK(2);
                mbar_wait(bar_addr(sb, B_FULL + ks), kph);
                const uint64_t dk = desc_sw128(slot_addr(sb, ks), 16);
                wg_fence();
#pragma unroll
                for (int k = 0; k < 16; k++)
                    wgmma_n64_ss(s, dp + (((k >> 2) * 16384 + (k & 3) * 32) >> 4), dk + (((k >> 2) * 8192 + (k & 3) * 32) >> 4), k > 0);
                wg_commit();
                if (w == 0) bar_arrive<2>(); else bar_arrive<3>();
                CLK(3);
                if (t > 0) {
                    wg_wait<1>();
                    if (lane == 0) release_pair(bar_addr(sb, B_EMPTY + vs), rank, wq == 0 ? 2 : 1);
                }
                CLK(4);
                wg_wait<0>();
                CLK(5);
                CLKALL(t);
                if (lane == 0) release_pair(bar_addr(sb, B_EMPTY + ks), rank);
                mbar_wait(bar_addr(sb, B_NORM + (t & 3)), (t >> 2) & 1);
                CLK(6);
                const uint32_t nb = sb + SM_NORM + (t & 3) * 256 + c * 8;
                float bias[16];
#pragma unroll
                for (int j = 0; j < 8; j++)
                    asm volatile("ld.shared.v2.f32 {%0, %1}, [%2];" : "=f"(bias[2 * j]), "=f"(bias[2 * j + 1]) : "r"(nb + j * 32) : "memory");
#pragma unroll
                for (int j = 0; j < 8; j++) {
                    const float bx = bias[2 * j], by = bias[2 * j + 1];
                    const float p00 = ex2(fmaf(s[4 * j], kC1, bx)), p01 = ex2(fmaf(s[4 * j + 1], kC1, by));
                    const float p10 = ex2(fmaf(s[4 * j + 2], kC1, bx)), p11 = ex2(fmaf(s[4 * j + 3], kC1, by));
                    ks0 += p00 + p01;
                    ks1 += p10 + p11;
                    p[2 * j] = pack_bf16(p00, p01);
                    p[2 * j + 1] = pack_bf16(p10, p11);
                }
                CLK(7);
                ks += 2;
                if (ks >= 5) { ks -= 5; kph ^= 1; }
            }
            if (w == 1) bar_sync<2>(); else bar_sync<3>();
            mbar_wait(bar_addr(sb, B_FULL + 0), 1);
            {
                const uint64_t dv = desc_sw128(slot_addr(sb, 0), 8192);
                wg_fence();
#pragma unroll
                for (int k = 0; k < 4; k++)
                    wgmma_n256_rs_tb(acc, p[4 * k], p[4 * k + 1], p[4 * k + 2], p[4 * k + 3], dv + ((k * 2048) >> 4), 1);
                wg_commit();
            }
            if (w == 0) bar_arrive<2>();
            wg_wait<0>();
            if (w == 1) bar_arrive<3>();
            PROFA(6); CLKS(11);
            ks0 += __shfl_xor_sync(0xffffffffu, ks0, 1); ks0 += __shfl_xor_sync(0xffffffffu, ks0, 2);
            ks1 += __shfl_xor_sync(0xffffffffu, ks1, 1); ks1 += __shfl_xor_sync(0xffffffffu, ks1, 2);
            if (c == 0) {
                asm volatile("st.shared.f32 [%0], %1;" :: "r"(sb + SM_KS + (w * 64 + wq * 16 + g) * 4), "f"(ks0) : "memory");
                asm volatile("st.shared.f32 [%0], %1;" :: "r"(sb + SM_KS + (w * 64 + wq * 16 + g + 8) * 4), "f"(ks1) : "memory");
            }
#pragma unroll
            for (int t = 0; t < 8; t++)
#pragma unroll
                for (int i = 0; i < 2; i++)
#pragma unroll
                    for (int jj = 0; jj < 4; jj++)
                        pk[8 * t + 4 * i + jj] = pack_bf16(acc[16 * t + 4 * jj + 2 * i], acc[16 * t + 4 * jj + 2 * i + 1]);
            auto load_a = [&]() {
                mbar_wait(bar_addr(sb, B_FULL + (w == 0 ? S_QA : S_QB)), 1);
                PROFW(8); CLKS(13);
                load_q_frags(f, qb0, qb1, slot_addr(sb, w == 0 ? S_QA : S_QB), wq, lane);
                asm volatile("fence.proxy.async.shared::cta;" ::: "memory");
                __syncwarp();
                if (lane == 0) mbar_arrive(bar_addr(sb, B_ACONS + w));
            };
            if (w == 0) {
                bar_sync<3>();
                stage(S_STG);
                PROFW(7); CLKS(12);
                load_a();
            } else {
                load_a();
            }
            PROFW(9); CLKS(14);
        }

        uint32_t phi[64], phib[64];
        const uint32_t qsb = slot_addr(sb, w == 0 ? S_QA : S_QB);
        {
            const uint32_t p0 = sb + SM_P0, po01 = slot_addr(sb, S_PO01), po23 = slot_addr(sb, S_PO23);
            float a[64];
            gemm3(a, f, p0, p0 + 32768);
            PROFW(10); CLKS(15);
            if (w == 1) {
                mbar_wait(bar_addr(sb, B_SFREE), 0);
                stage(S_STG);
                PROFW(7); CLKS(12);
            }
            wg_wait<0>();
            PROFW(11); CLKS(16);
            exp_to_regs<0>(phi, a, qb0, qb1);
            PROFW(12); CLKS(17);
            mbar_wait(bar_addr(sb, B_PO01), 0);
            mbar_wait(bar_addr(sb, B_PO23), 0);
            PROFW(13); CLKS(18);
            gemm3(a, f, po01, po23);
            PROFW(14); CLKS(19);
            wg_wait<0>();
            PROFW(16); CLKS(20);
            exp_to_regs<32>(phi, a, qb0, qb1);
            mbar_wait(bar_addr(sb, B_FULL + (w == 0 ? S_QA : S_QB)), 0);
            PROFW(17); CLKS(21);
            float s0 = 0.f, s1 = 0.f;
            wg_fence();
            gemm3_ss<0>(a, qsb, p0);
            tile_sumsq<0>(s0, s1, qsb, wq, lane);
            gemm3_ss<8>(a, qsb, p0 + 32768);
            wg_commit();
            tile_sumsq<8>(s0, s1, qsb, wq, lane);
            s0 += __shfl_xor_sync(0xffffffffu, s0, 1); s1 += __shfl_xor_sync(0xffffffffu, s1, 1);
            s0 += __shfl_xor_sync(0xffffffffu, s0, 2); s1 += __shfl_xor_sync(0xffffffffu, s1, 2);
            qb0 = fmaf(s0, kC2, kC3);
            qb1 = fmaf(s1, kC2, kC3);
            PROFW(18); CLKS(22);
            wg_wait<0>();
            PROFW(19); CLKS(23);
            if (lane == 0) mbar_arrive(bar_addr(sb, B_P0DEAD));
            exp_to_regs<0>(phib, a, qb0, qb1);
            wg_fence();
            gemm3_ss<0>(a, qsb, po01);
            gemm3_ss<8>(a, qsb, po23);
            wg_commit();
            wg_wait<0>();
            PROFW(21); CLKS(24);
            if (lane == 0) {
                mbar_arrive(bar_addr(sb, B_PDEAD));
                if (w == 0) mbar_arrive(bar_addr(sb, B_B0DEAD));
            }
            exp_to_regs<32>(phib, a, qb0, qb1);
            PROFW(22); CLKS(25);
        }
        asm volatile("barrier.cluster.arrive.relaxed.aligned;" ::: "memory");
        {
            const uint32_t kvb[4] = {slot_addr(sb, S_STG), sb + SM_P0, sb + SM_P0 + 32768, slot_addr(sb, S_PO01)};
            const uint32_t mo = rank * 128 * 128, mx = (rank ^ 1) * 128 * 128;
            const int orow = h * kSeq + sc * 512 + rank * 256 + w * 64 + wq * 16 + g;
            __nv_bfloat16* pA = out + (size_t)orow * kDim + c * 8;
            __nv_bfloat16* pB = pA + 128 * kDim;
            float iA0, iA1, iB0, iB1;
            auto take_turn = [&](bool first) { if (w == 1) bar_sync<2>(); else if (!first) bar_sync<3>(); };
            auto give_turn = [&](bool last) { if (w == 0) bar_arrive<2>(); else if (!last) bar_arrive<3>(); };
            {
                float e[36];
                const uint32_t lbo = slot_addr(sb, S_QA) - slot_addr(sb, S_STG);
                auto tile0 = [&](const uint32_t (&ph)[64], bool first) {
                    const uint64_t d0 = desc_sw128(kvb[0] + mo, lbo), d1 = desc_sw128(kvb[0] + mx, lbo);
                    take_turn(first);
                    wg_fence();
#pragma unroll
                    for (int k = 0; k < 16; k++)
                        wgmma_n72_rs_tb(e, ph[4 * k], ph[4 * k + 1], ph[4 * k + 2], ph[4 * k + 3], (k < 8 ? d0 : d1) + (((k & 7) * 2048) >> 4), k > 0);
                    wg_commit();
                    give_turn(false);
                    wg_wait<0>();
                };
                mbar_wait(bar_addr(sb, B_KV + 0), 0);
                mbar_wait(bar_addr(sb, B_KSUM), 0);
                PROFA(23); CLKS(26);
                tile0(phi, true);
                iA0 = __fdividef(1.f, e[32] + 1e-6f);
                iA1 = __fdividef(1.f, e[34] + 1e-6f);
                store_out(e, iA0, iA1, pA);
                CLKG4(0);
                tile0(phib, false);
                iB0 = __fdividef(1.f, e[32] + 1e-6f);
                iB1 = __fdividef(1.f, e[34] + 1e-6f);
                store_out(e, iB0, iB1, pB);
                CLKG4(1);
            }
#pragma unroll
            for (int i = 2; i < 8; i++) {
                const int b = i >> 1;
                float o[32];
                const uint64_t d0 = desc_sw128(kvb[b] + mo, 16), d1 = desc_sw128(kvb[b] + mx, 16);
                if (!(i & 1)) mbar_wait(bar_addr(sb, B_KV + b), 0);
                take_turn(false);
                wg_fence();
#pragma unroll
                for (int k = 0; k < 16; k++) {
                    const uint32_t (&ph)[64] = (i & 1) ? phib : phi;
                    wgmma_n64_rs_tb(o, ph[4 * k], ph[4 * k + 1], ph[4 * k + 2], ph[4 * k + 3], (k < 8 ? d0 : d1) + (((k & 7) * 2048) >> 4), k > 0);
                }
                wg_commit();
                give_turn(i == 7);
                wg_wait<0>();
                if (i & 1) store_out(o, iB0, iB1, pB + b * 64); else store_out(o, iA0, iA1, pA + b * 64);
                CLKG4(i);
            }
        }
        PROFA(24);
        CLKS(27);
        asm volatile("barrier.cluster.wait.aligned;" ::: "memory");
    }
}

typedef CUresult (*EncodeTiledFn)(CUtensorMap*, CUtensorMapDataType, cuuint32_t, void*, const cuuint64_t*, const cuuint64_t*,
                                  const cuuint32_t*, const cuuint32_t*, CUtensorMapInterleave, CUtensorMapSwizzle,
                                  CUtensorMapL2promotion, CUtensorMapFloatOOBfill);

bool make_map(EncodeTiledFn enc, CUtensorMap* m, const void* base, uint64_t rows, uint32_t box_rows) {
    cuuint64_t dims[3] = {64, rows, 4};
    cuuint64_t strides[2] = {512, 128};
    cuuint32_t box[3] = {64, box_rows, 2};
    cuuint32_t es[3] = {1, 1, 1};
    return enc(m, CU_TENSOR_MAP_DATA_TYPE_BFLOAT16, 3, const_cast<void*>(base), dims, strides, box, es,
               CU_TENSOR_MAP_INTERLEAVE_NONE, CU_TENSOR_MAP_SWIZZLE_128B, CU_TENSOR_MAP_L2_PROMOTION_L2_256B,
               CU_TENSOR_MAP_FLOAT_OOB_FILL_NONE) == CUDA_SUCCESS;
}

}

extern "C" void kernel_launch(void* const* d_in, const int* in_sizes, int n_in, void* d_out, int out_size) {
    (void)in_sizes; (void)n_in; (void)out_size;
    static EncodeTiledFn enc = nullptr;
    if (!enc) {
        void* fn = nullptr;
        cudaDriverEntryPointQueryResult qr;
        if (cudaGetDriverEntryPoint("cuTensorMapEncodeTiled", &fn, cudaEnableDefault, &qr) != cudaSuccess || !fn) return;
        enc = (EncodeTiledFn)fn;
        cudaFuncSetAttribute(performer_kernel, cudaFuncAttributeMaxDynamicSharedMemorySize, SM_TOTAL);
    }
    CUtensorMap tq, tk, tv, tp;
    if (!make_map(enc, &tq, d_in[0], kHeads * kSeq, 64) || !make_map(enc, &tk, d_in[1], kHeads * kSeq, 64) ||
        !make_map(enc, &tv, d_in[2], kHeads * kSeq, 64) || !make_map(enc, &tp, d_in[3], 256, 128)) return;
    performer_kernel<<<128, 384, SM_TOTAL, cudaStreamPerThread>>>(tq, tk, tv, tp, (const uint8_t*)d_in[1], (const uint8_t*)d_in[3],
                                                                    (__nv_bfloat16*)d_out);
}
```

```cpp
#include <cuda_runtime.h>
#include <cuda_bf16.h>
#include <cuda.h>
#include <stdint.h>

namespace {

constexpr int kHeads = 16;
constexpr int kSeq = 2048;
constexpr int kDim = 256;

constexpr uint32_t SM_P0 = 0;
constexpr uint32_t SM_SLOT = 65536;
constexpr uint32_t SLOT_BYTES = 32768;
constexpr uint32_t SM_BAR = SM_SLOT + 5 * SLOT_BYTES;
constexpr uint32_t SM_NORM = SM_BAR + 512;
constexpr uint32_t SM_KS = SM_NORM + 1024;
constexpr uint32_t SM_TOTAL = SM_KS + 512;

constexpr int S_STG = 0, S_QA = 1, S_PO23 = 2, S_PO01 = 3, S_QB = 4;

constexpr int B_PROJ = 0;
constexpr int B_FULL = 1;
constexpr int B_EMPTY = 6;
constexpr int B_NORM = 11;
constexpr int B_KV = 15;
constexpr int B_STG = 19;
constexpr int B_GO = 21;
constexpr int B_ACONS = 22;
constexpr int B_SFREE = 24;
constexpr int B_PO01 = 26;
constexpr int B_PO23 = 27;
constexpr int B_ZERO = 28;
constexpr int B_PDEAD = 29;
constexpr int B_B0DEAD = 30;
constexpr int B_KSUM = 31;
constexpr int B_DUMPED = 32;
constexpr int B_P0DEAD = 33;

constexpr int kSpinLimit = 1 << 21;

__device__ uint4 g_kvacc[kHeads * 8192];
__device__ float g_ksum[kHeads * 256];
__device__ unsigned g_flag_zero[kHeads * 32];
__device__ unsigned g_flag_dump[kHeads * 64];
#define PROF(i) do {} while (0)
#define PROFW(i) do {} while (0)
#define PROFA(i) do {} while (0)
#define PROFS(i) do {} while (0)
#define CLK(i) do {} while (0)
#define CLKS(i) do {} while (0)
#define CLKP(i) do {} while (0)
#define CLKALL(i) do {} while (0)
#define CLKG4(i) do {} while (0)

__device__ __forceinline__ void mbar_init(uint32_t bar, uint32_t cnt) {
    asm volatile("mbarrier.init.shared::cta.b64 [%0], %1;" :: "r"(bar), "r"(cnt) : "memory");
}
__device__ __forceinline__ void mbar_expect_tx(uint32_t bar, uint32_t bytes) {
    asm volatile("mbarrier.arrive.expect_tx.shared::cta.b64 _, [%0], %1;" :: "r"(bar), "r"(bytes) : "memory");
}
__device__ __forceinline__ void mbar_arrive(uint32_t bar) {
    asm volatile("mbarrier.arrive.shared::cta.b64 _, [%0];" :: "r"(bar) : "memory");
}
__device__ __forceinline__ uint32_t mbar_arrive_lane0(uint32_t bar, int lane) {
    uint32_t lo;
    asm volatile("{\n.reg .pred p;\n.reg .b64 st;\n.reg .b32 hi;\nmov.b64 st, 0;\nsetp.eq.s32 p, %2, 0;\n"
                 "@p mbarrier.arrive.shared::cta.b64 st, [%1];\nmov.b64 {%0, hi}, st;\n}" : "=r"(lo) : "r"(bar), "r"(lane) : "memory");
    return lo;
}
__device__ __forceinline__ void mbar_arrive_n(uint32_t bar, uint32_t cta, uint32_t count) {
    asm volatile("{\n.reg .b32 ra;\nmapa.shared::cluster.u32 ra, %0, %1;\n"
                 "mbarrier.arrive.shared::cluster.b64 _, [ra], %2;\n}" :: "r"(bar), "r"(cta), "r"(count) : "memory");
}
__device__ __forceinline__ void mbar_wait(uint32_t bar, uint32_t parity) {
    uint32_t ok;
    int it = 0;
    do {
        asm volatile("{\n.reg .pred p;\nmbarrier.try_wait.parity.shared::cta.b64 p, [%1], %2;\nselp.u32 %0, 1, 0, p;\n}"
                     : "=r"(ok) : "r"(bar), "r"(parity) : "memory");
    } while (!ok && ++it < kSpinLimit);
}
__device__ __forceinline__ void tma_load(uint32_t dst, const CUtensorMap* tm, uint32_t bar, int row, int blk) {
    asm volatile("cp.async.bulk.tensor.3d.shared::cluster.global.mbarrier::complete_tx::bytes [%0], [%1, {%3, %4, %5}], [%2];"
                 :: "r"(dst), "l"(tm), "r"(bar), "r"(0), "r"(row), "r"(blk) : "memory");
}
__device__ __forceinline__ uint64_t policy_evict_first() {
    uint64_t p;
    asm volatile("createpolicy.fractional.L2::evict_first.b64 %0, 1.0;" : "=l"(p));
    return p;
}
__device__ __forceinline__ void tma_load_ef(uint32_t dst, const CUtensorMap* tm, uint32_t bar, int row, int blk, uint64_t pol) {
    asm volatile("cp.async.bulk.tensor.3d.shared::cluster.global.mbarrier::complete_tx::bytes.L2::cache_hint [%0], [%1, {%3, %4, %5}], [%2], %6;"
                 :: "r"(dst), "l"(tm), "r"(bar), "r"(0), "r"(row), "r"(blk), "l"(pol) : "memory");
}
__device__ __forceinline__ void tma_load_mc(uint32_t dst, const CUtensorMap* tm, uint32_t bar, int row, int blk, uint64_t pol) {
    asm volatile("cp.async.bulk.tensor.3d.shared::cluster.global.mbarrier::complete_tx::bytes.multicast::cluster.L2::cache_hint [%0], [%1, {%3, %4, %5}], [%2], %6, %7;"
                 :: "r"(dst), "l"(tm), "r"(bar), "r"(0), "r"(row), "r"(blk), "h"((uint16_t)3), "l"(pol) : "memory");
}
__device__ __forceinline__ void bulk_load(uint32_t dst, const void* src, uint32_t bytes, uint32_t bar) {
    asm volatile("cp.async.bulk.shared::cluster.global.mbarrier::complete_tx::bytes [%0], [%1], %2, [%3];"
                 :: "r"(dst), "l"(src), "r"(bytes), "r"(bar) : "memory");
}
__device__ __forceinline__ void wg_fence() { asm volatile("wgmma.fence.sync.aligned;" ::: "memory"); }
__device__ __forceinline__ void wg_commit() { asm volatile("wgmma.commit_group.sync.aligned;" ::: "memory"); }
template <int N> __device__ __forceinline__ void wg_wait() { asm volatile("wgmma.wait_group.sync.aligned %0;" :: "n"(N) : "memory"); }

__device__ __forceinline__ uint64_t desc_sw128(uint32_t addr, uint32_t lbo) {
    asm volatile("" : "+r"(addr));
    return (uint64_t)((addr & 0x3FFFF) >> 4) | ((uint64_t)(lbo >> 4) << 16) | ((uint64_t)(1024 >> 4) << 32) | (1ull << 62);
}
__device__ __forceinline__ uint32_t pack_bf16(float lo, float hi) {
    uint32_t r;
    asm("cvt.rn.bf16x2.f32 %0, %1, %2;" : "=r"(r) : "f"(hi), "f"(lo));
    return r;
}
__device__ __forceinline__ float ex2(float x) {
    float y;
    asm("ex2.approx.ftz.f32 %0, %1;" : "=f"(y) : "f"(x));
    return y;
}
__device__ __forceinline__ unsigned ld_relaxed_gpu(const unsigned* p) {
    unsigned v;
    asm volatile("ld.relaxed.gpu.global.u32 %0, [%1];" : "=r"(v) : "l"(p) : "memory");
    return v;
}
__device__ __forceinline__ void fence_gpu() { asm volatile("fence.acq_rel.gpu;" ::: "memory"); }
__device__ __forceinline__ void red_add_u32(unsigned* p, unsigned v) {
    asm volatile("red.relaxed.gpu.global.add.u32 [%0], %1;" :: "l"(p), "r"(v) : "memory");
}
__device__ __forceinline__ unsigned ld_acquire_gpu(const unsigned* p) {
    unsigned v;
    asm volatile("ld.acquire.gpu.global.u32 %0, [%1];" : "=r"(v) : "l"(p) : "memory");
    return v;
}
__device__ __forceinline__ void spin_flag(const unsigned* p, unsigned target) {
    int it = 0;
    while ((int)(ld_acquire_gpu(p) - target) < 0 && ++it < kSpinLimit) {}
}
template <int R> __device__ __forceinline__ void reg_alloc() { asm volatile("setmaxnreg.inc.sync.aligned.u32 %0;" :: "n"(R)); }
template <int R> __device__ __forceinline__ void reg_dealloc() { asm volatile("setmaxnreg.dec.sync.aligned.u32 %0;" :: "n"(R)); }

template <int N>
__device__ __forceinline__ void wgmma_n64_ss(float (&d)[N], uint64_t da, uint64_t db, int scale_d) {
    asm volatile("{\n.reg .pred p;\nsetp.ne.b32 p, %34, 0;\n"
        "wgmma.mma_async.sync.aligned.m64n64k16.f32.bf16.bf16 "
        "{%0, %1, %2, %3, %4, %5, %6, %7, %8, %9, %10, %11, %12, %13, %14, %15, "
        "%16, %17, %18, %19, %20, %21, %22, %23, %24, %25, %26, %27, %28, %29, %30, %31}, "
        "%32, %33, p, 1, 1, 0, 0;\n}\n"
        : "+f"(d[0]), "+f"(d[1]), "+f"(d[2]), "+f"(d[3]), "+f"(d[4]), "+f"(d[5]), "+f"(d[6]), "+f"(d[7]),
          "+f"(d[8]), "+f"(d[9]), "+f"(d[10]), "+f"(d[11]), "+f"(d[12]), "+f"(d[13]), "+f"(d[14]), "+f"(d[15]),
          "+f"(d[16]), "+f"(d[17]), "+f"(d[18]), "+f"(d[19]), "+f"(d[20]), "+f"(d[21]), "+f"(d[22]), "+f"(d[23]),
          "+f"(d[24]), "+f"(d[25]), "+f"(d[26]), "+f"(d[27]), "+f"(d[28]), "+f"(d[29]), "+f"(d[30]), "+f"(d[31])
        : "l"(da), "l"(db), "r"(scale_d));
}
template <int N>
__device__ __forceinline__ void wgmma_n64_rs_tb(float (&d)[N], uint32_t a0, uint32_t a1, uint32_t a2, uint32_t a3, uint64_t db, int scale_d) {
    asm volatile("{\n.reg .pred p;\nsetp.ne.b32 p, %37, 0;\n"
        "wgmma.mma_async.sync.aligned.m64n64k16.f32.bf16.bf16 "
        "{%0, %1, %2, %3, %4, %5, %6, %7, %8, %9, %10, %11, %12, %13, %14, %15, "
        "%16, %17, %18, %19, %20, %21, %22, %23, %24, %25, %26, %27, %28, %29, %30, %31}, "
        "{%32, %33, %34, %35}, %36, p, 1, 1, 1;\n}\n"
        : "+f"(d[0]), "+f"(d[1]), "+f"(d[2]), "+f"(d[3]), "+f"(d[4]), "+f"(d[5]), "+f"(d[6]), "+f"(d[7]),
          "+f"(d[8]), "+f"(d[9]), "+f"(d[10]), "+f"(d[11]), "+f"(d[12]), "+f"(d[13]), "+f"(d[14]), "+f"(d[15]),
          "+f"(d[16]), "+f"(d[17]), "+f"(d[18]), "+f"(d[19]), "+f"(d[20]), "+f"(d[21]), "+f"(d[22]), "+f"(d[23]),
          "+f"(d[24]), "+f"(d[25]), "+f"(d[26]), "+f"(d[27]), "+f"(d[28]), "+f"(d[29]), "+f"(d[30]), "+f"(d[31])
        : "r"(a0), "r"(a1), "r"(a2), "r"(a3), "l"(db), "r"(scale_d));
}
template <int N>
__device__ __forceinline__ void wgmma_n72_rs_tb(float (&d)[N], uint32_t a0, uint32_t a1, uint32_t a2, uint32_t a3, uint64_t db, int scale_d) {
    asm volatile("{\n.reg .pred p;\nsetp.ne.b32 p, %41, 0;\n"
        "wgmma.mma_async.sync.aligned.m64n72k16.f32.bf16.bf16 "
        "{%0, %1, %2, %3, %4, %5, %6, %7, %8, %9, %10, %11, %12, %13, %14, %15, "
        "%16, %17, %18, %19, %20, %21, %22, %23, %24, %25, %26, %27, %28, %29, %30, %31, "
        "%32, %33, %34, %35}, "
        "{%36, %37, %38, %39}, %40, p, 1, 1, 1;\n}\n"
        : "+f"(d[0]), "+f"(d[1]), "+f"(d[2]), "+f"(d[3]), "+f"(d[4]), "+f"(d[5]), "+f"(d[6]), "+f"(d[7]),
          "+f"(d[8]), "+f"(d[9]), "+f"(d[10]), "+f"(d[11]), "+f"(d[12]), "+f"(d[13]), "+f"(d[14]), "+f"(d[15]),
          "+f"(d[16]), "+f"(d[17]), "+f"(d[18]), "+f"(d[19]), "+f"(d[20]), "+f"(d[21]), "+f"(d[22]), "+f"(d[23]),
          "+f"(d[24]), "+f"(d[25]), "+f"(d[26]), "+f"(d[27]), "+f"(d[28]), "+f"(d[29]), "+f"(d[30]), "+f"(d[31]),
          "+f"(d[32]), "+f"(d[33]), "+f"(d[34]), "+f"(d[35])
        : "r"(a0), "r"(a1), "r"(a2), "r"(a3), "l"(db), "r"(scale_d));
}
template <int N>
__device__ __forceinline__ void wgmma_n128_rs(float (&d)[N], uint32_t a0, uint32_t a1, uint32_t a2, uint32_t a3, uint64_t db, int scale_d) {
    asm volatile("{\n.reg .pred p;\nsetp.ne.b32 p, %69, 0;\n"
        "wgmma.mma_async.sync.aligned.m64n128k16.f32.bf16.bf16 "
        "{%0, %1, %2, %3, %4, %5, %6, %7, %8, %9, %10, %11, %12, %13, %14, %15, "
        "%16, %17, %18, %19, %20, %21, %22, %23, %24, %25, %26, %27, %28, %29, %30, %31, "
        "%32, %33, %34, %35, %36, %37, %38, %39, %40, %41, %42, %43, %44, %45, %46, %47, "
        "%48, %49, %50, %51, %52, %53, %54, %55, %56, %57, %58, %59, %60, %61, %62, %63}, "
        "{%64, %65, %66, %67}, %68, p, 1, 1, 0;\n}\n"
        : "+f"(d[0]), "+f"(d[1]), "+f"(d[2]), "+f"(d[3]), "+f"(d[4]), "+f"(d[5]), "+f"(d[6]), "+f"(d[7]),
          "+f"(d[8]), "+f"(d[9]), "+f"(d[10]), "+f"(d[11]), "+f"(d[12]), "+f"(d[13]), "+f"(d[14]), "+f"(d[15]),
          "+f"(d[16]), "+f"(d[17]), "+f"(d[18]), "+f"(d[19]), "+f"(d[20]), "+f"(d[21]), "+f"(d[22]), "+f"(d[23]),
          "+f"(d[24]), "+f"(d[25]), "+f"(d[26]), "+f"(d[27]), "+f"(d[28]), "+f"(d[29]), "+f"(d[30]), "+f"(d[31]),
          "+f"(d[32]), "+f"(d[33]), "+f"(d[34]), "+f"(d[35]), "+f"(d[36]), "+f"(d[37]), "+f"(d[38]), "+f"(d[39]),
          "+f"(d[40]), "+f"(d[41]), "+f"(d[42]), "+f"(d[43]), "+f"(d[44]), "+f"(d[45]), "+f"(d[46]), "+f"(d[47]),
          "+f"(d[48]), "+f"(d[49]), "+f"(d[50]), "+f"(d[51]), "+f"(d[52]), "+f"(d[53]), "+f"(d[54]), "+f"(d[55]),
          "+f"(d[56]), "+f"(d[57]), "+f"(d[58]), "+f"(d[59]), "+f"(d[60]), "+f"(d[61]), "+f"(d[62]), "+f"(d[63])
        : "r"(a0), "r"(a1), "r"(a2), "r"(a3), "l"(db), "r"(scale_d));
}
template <int N>
__device__ __forceinline__ void wgmma_n128_ss(float (&d)[N], uint64_t da, uint64_t db, int scale_d) {
    asm volatile("{\n.reg .pred p;\nsetp.ne.b32 p, %66, 0;\n"
        "wgmma.mma_async.sync.aligned.m64n128k16.f32.bf16.bf16 "
        "{%0, %1, %2, %3, %4, %5, %6, %7, %8, %9, %10, %11, %12, %13, %14, %15, "
        "%16, %17, %18, %19, %20, %21, %22, %23, %24, %25, %26, %27, %28, %29, %30, %31, "
        "%32, %33, %34, %35, %36, %37, %38, %39, %40, %41, %42, %43, %44, %45, %46, %47, "
        "%48, %49, %50, %51, %52, %53, %54, %55, %56, %57, %58, %59, %60, %61, %62, %63}, "
        "%64, %65, p, 1, 1, 0, 0;\n}\n"
        : "+f"(d[0]), "+f"(d[1]), "+f"(d[2]), "+f"(d[3]), "+f"(d[4]), "+f"(d[5]), "+f"(d[6]), "+f"(d[7]),
          "+f"(d[8]), "+f"(d[9]), "+f"(d[10]), "+f"(d[11]), "+f"(d[12]), "+f"(d[13]), "+f"(d[14]), "+f"(d[15]),
          "+f"(d[16]), "+f"(d[17]), "+f"(d[18]), "+f"(d[19]), "+f"(d[20]), "+f"(d[21]), "+f"(d[22]), "+f"(d[23]),
          "+f"(d[24]), "+f"(d[25]), "+f"(d[26]), "+f"(d[27]), "+f"(d[28]), "+f"(d[29]), "+f"(d[30]), "+f"(d[31]),
          "+f"(d[32]), "+f"(d[33]), "+f"(d[34]), "+f"(d[35]), "+f"(d[36]), "+f"(d[37]), "+f"(d[38]), "+f"(d[39]),
          "+f"(d[40]), "+f"(d[41]), "+f"(d[42]), "+f"(d[43]), "+f"(d[44]), "+f"(d[45]), "+f"(d[46]), "+f"(d[47]),
          "+f"(d[48]), "+f"(d[49]), "+f"(d[50]), "+f"(d[51]), "+f"(d[52]), "+f"(d[53]), "+f"(d[54]), "+f"(d[55]),
          "+f"(d[56]), "+f"(d[57]), "+f"(d[58]), "+f"(d[59]), "+f"(d[60]), "+f"(d[61]), "+f"(d[62]), "+f"(d[63])
        : "l"(da), "l"(db), "r"(scale_d));
}
template <int N>
__device__ __forceinline__ void wgmma_n256_rs_tb(float (&d)[N], uint32_t a0, uint32_t a1, uint32_t a2, uint32_t a3, uint64_t db, int scale_d) {
    asm volatile("{\n.reg .pred p;\nsetp.ne.b32 p, %133, 0;\n"
        "wgmma.mma_async.sync.aligned.m64n256k16.f32.bf16.bf16 "
        "{%0, %1, %2, %3, %4, %5, %6, %7, %8, %9, %10, %11, %12, %13, %14, %15, "
        "%16, %17, %18, %19, %20, %21, %22, %23, %24, %25, %26, %27, %28, %29, %30, %31, "
        "%32, %33, %34, %35, %36, %37, %38, %39, %40, %41, %42, %43, %44, %45, %46, %47, "
        "%48, %49, %50, %51, %52, %53, %54, %55, %56, %57, %58, %59, %60, %61, %62, %63, "
        "%64, %65, %66, %67, %68, %69, %70, %71, %72, %73, %74, %75, %76, %77, %78, %79, "
        "%80, %81, %82, %83, %84, %85, %86, %87, %88, %89, %90, %91, %92, %93, %94, %95, "
        "%96, %97, %98, %99, %100, %101, %102, %103, %104, %105, %106, %107, %108, %109, %110, %111, "
        "%112, %113, %114, %115, %116, %117, %118, %119, %120, %121, %122, %123, %124, %125, %126, %127}, "
        "{%128, %129, %130, %131}, %132, p, 1, 1, 1;\n}\n"
        : "+f"(d[0]), "+f"(d[1]), "+f"(d[2]), "+f"(d[3]), "+f"(d[4]), "+f"(d[5]), "+f"(d[6]), "+f"(d[7]),
          "+f"(d[8]), "+f"(d[9]), "+f"(d[10]), "+f"(d[11]), "+f"(d[12]), "+f"(d[13]), "+f"(d[14]), "+f"(d[15]),
          "+f"(d[16]), "+f"(d[17]), "+f"(d[18]), "+f"(d[19]), "+f"(d[20]), "+f"(d[21]), "+f"(d[22]), "+f"(d[23]),
          "+f"(d[24]), "+f"(d[25]), "+f"(d[26]), "+f"(d[27]), "+f"(d[28]), "+f"(d[29]), "+f"(d[30]), "+f"(d[31]),
          "+f"(d[32]), "+f"(d[33]), "+f"(d[34]), "+f"(d[35]), "+f"(d[36]), "+f"(d[37]), "+f"(d[38]), "+f"(d[39]),
          "+f"(d[40]), "+f"(d[41]), "+f"(d[42]), "+f"(d[43]), "+f"(d[44]), "+f"(d[45]), "+f"(d[46]), "+f"(d[47]),
          "+f"(d[48]), "+f"(d[49]), "+f"(d[50]), "+f"(d[51]), "+f"(d[52]), "+f"(d[53]), "+f"(d[54]), "+f"(d[55]),
          "+f"(d[56]), "+f"(d[57]), "+f"(d[58]), "+f"(d[59]), "+f"(d[60]), "+f"(d[61]), "+f"(d[62]), "+f"(d[63]),
          "+f"(d[64]), "+f"(d[65]), "+f"(d[66]), "+f"(d[67]), "+f"(d[68]), "+f"(d[69]), "+f"(d[70]), "+f"(d[71]),
          "+f"(d[72]), "+f"(d[73]), "+f"(d[74]), "+f"(d[75]), "+f"(d[76]), "+f"(d[77]), "+f"(d[78]), "+f"(d[79]),
          "+f"(d[80]), "+f"(d[81]), "+f"(d[82]), "+f"(d[83]), "+f"(d[84]), "+f"(d[85]), "+f"(d[86]), "+f"(d[87]),
          "+f"(d[88]), "+f"(d[89]), "+f"(d[90]), "+f"(d[91]), "+f"(d[92]), "+f"(d[93]), "+f"(d[94]), "+f"(d[95]),
          "+f"(d[96]), "+f"(d[97]), "+f"(d[98]), "+f"(d[99]), "+f"(d[100]), "+f"(d[101]), "+f"(d[102]), "+f"(d[103]),
          "+f"(d[104]), "+f"(d[105]), "+f"(d[106]), "+f"(d[107]), "+f"(d[108]), "+f"(d[109]), "+f"(d[110]), "+f"(d[111]),
          "+f"(d[112]), "+f"(d[113]), "+f"(d[114]), "+f"(d[115]), "+f"(d[116]), "+f"(d[117]), "+f"(d[118]), "+f"(d[119]),
          "+f"(d[120]), "+f"(d[121]), "+f"(d[122]), "+f"(d[123]), "+f"(d[124]), "+f"(d[125]), "+f"(d[126]), "+f"(d[127])
        : "r"(a0), "r"(a1), "r"(a2), "r"(a3), "l"(db), "r"(scale_d));
}

constexpr float kC1 = 0.25f * 1.4426950408889634f;
constexpr float kC2 = -1.4426950408889634f / 32.0f;
constexpr float kC3 = -4.0f;

template <int V> struct Int { static constexpr int value = V; };
__device__ __forceinline__ uint32_t slot_addr(uint32_t sb, int s) { return sb + SM_SLOT + s * SLOT_BYTES; }
__device__ __forceinline__ uint32_t bar_addr(uint32_t sb, int b) { return sb + SM_BAR + b * 8; }

__device__ __forceinline__ void release_pair(uint32_t bar, uint32_t rank, uint32_t count = 1) {
    mbar_arrive_n(bar, rank, count);
    mbar_arrive_n(bar, rank ^ 1, count);
}

__device__ __forceinline__ float row_bias(uint32_t tile, int row, int half) {
    const uint32_t base = tile + half * 16384 + row * 128;
    const uint32_t sw = ((row & 7) ^ (half << 2)) << 4;
    float s0 = 0.f, s1 = 0.f, s2 = 0.f, s3 = 0.f;
#pragma unroll
    for (int bt = 0; bt < 4; bt++) {
        uint32_t x[4][4];
#pragma unroll
        for (int i = 0; i < 4; i++)
            asm volatile("ld.shared.v4.u32 {%0, %1, %2, %3}, [%4];" : "=r"(x[i][0]), "=r"(x[i][1]), "=r"(x[i][2]), "=r"(x[i][3])
                         : "r"(base + (bt >> 1) * 8192 + ((((bt & 1) * 4 + i) << 4) ^ sw)));
#pragma unroll
        for (int i = 0; i < 4; i++) {
            float a;
            a = __uint_as_float(x[i][0] << 16); s0 = fmaf(a, a, s0);
            a = __uint_as_float(x[i][0] & 0xffff0000u); s1 = fmaf(a, a, s1);
            a = __uint_as_float(x[i][1] << 16); s2 = fmaf(a, a, s2);
            a = __uint_as_float(x[i][1] & 0xffff0000u); s3 = fmaf(a, a, s3);
            a = __uint_as_float(x[i][2] << 16); s0 = fmaf(a, a, s0);
            a = __uint_as_float(x[i][2] & 0xffff0000u); s1 = fmaf(a, a, s1);
            a = __uint_as_float(x[i][3] << 16); s2 = fmaf(a, a, s2);
            a = __uint_as_float(x[i][3] & 0xffff0000u); s3 = fmaf(a, a, s3);
        }
    }
    float s = (s0 + s1) + (s2 + s3);
    s += __shfl_xor_sync(0xffffffffu, s, 1);
    return fmaf(s, kC2, kC3);
}
__device__ __forceinline__ void st_async_f32(uint32_t addr, float v, uint32_t bar, uint32_t cta) {
    asm volatile("{\n.reg .b32 ra, rb;\nmapa.shared::cluster.u32 ra, %0, %3;\nmapa.shared::cluster.u32 rb, %2, %3;\n"
                 "st.async.weak.shared::cluster.mbarrier::complete_tx::bytes.f32 [ra], %1, [rb];\n}"
                 :: "r"(addr), "f"(v), "r"(bar), "r"(cta) : "memory");
}

__device__ __forceinline__ void load_q_frags(uint32_t (&f)[64], float& qb0, float& qb1, uint32_t tile, int wq, int lane) {
    const int row = wq * 16 + (lane & 7) + ((lane >> 3) & 1) * 8;
    const uint32_t base = tile + row * 128;
#pragma unroll
    for (int k = 0; k < 16; k++) {
        const int chunk = 2 * k + (lane >> 4);
        asm volatile("ldmatrix.sync.aligned.m8n8.x4.shared.b16 {%0, %1, %2, %3}, [%4];"
                     : "=r"(f[4 * k]), "=r"(f[4 * k + 1]), "=r"(f[4 * k + 2]), "=r"(f[4 * k + 3])
                     : "r"(base + (k >> 2) * 8192 + (((chunk & 7) ^ (row & 7)) << 4)));
    }
    float s0 = 0.f, s1 = 0.f, s2 = 0.f, s3 = 0.f;
#pragma unroll
    for (int k = 0; k < 32; k++) {
        float a;
        a = __uint_as_float(f[2 * k] << 16); s0 = fmaf(a, a, s0);
        a = __uint_as_float(f[2 * k] & 0xffff0000u); s1 = fmaf(a, a, s1);
        a = __uint_as_float(f[2 * k + 1] << 16); s2 = fmaf(a, a, s2);
        a = __uint_as_float(f[2 * k + 1] & 0xffff0000u); s3 = fmaf(a, a, s3);
    }
    s0 += s1; s2 += s3;
    s0 += __shfl_xor_sync(0xffffffffu, s0, 1); s2 += __shfl_xor_sync(0xffffffffu, s2, 1);
    s0 += __shfl_xor_sync(0xffffffffu, s0, 2); s2 += __shfl_xor_sync(0xffffffffu, s2, 2);
    qb0 = fmaf(s0, kC2, kC3);
    qb1 = fmaf(s2, kC2, kC3);
}
__device__ __forceinline__ void gemm3(float (&d)[64], const uint32_t (&f)[64], uint32_t b01, uint32_t b23) {
    const uint64_t d0 = desc_sw128(b01, 16), d1 = desc_sw128(b23, 16);
    wg_fence();
#pragma unroll
    for (int k = 0; k < 16; k++)
        wgmma_n128_rs(d, f[4 * k], f[4 * k + 1], f[4 * k + 2], f[4 * k + 3],
                      (k < 8 ? d0 : d1) + ((((k >> 2) & 1) * 16384 + (k & 3) * 32) >> 4), k > 0);
    wg_commit();
}
template <int K0>
__device__ __forceinline__ void gemm3_ss(float (&d)[64], uint32_t qs, uint32_t pb) {
    const uint64_t da = desc_sw128(qs + (K0 >> 2) * 8192, 16), db = desc_sw128(pb, 16);
#pragma unroll
    for (int k = 0; k < 8; k++)
        wgmma_n128_ss(d, da + (((k >> 2) * 8192 + (k & 3) * 32) >> 4), db + (((k >> 2) * 16384 + (k & 3) * 32) >> 4), (K0 + k) > 0);
}
template <int K0>
__device__ __forceinline__ void tile_sumsq(float& s0, float& s1, uint32_t tile, int wq, int lane) {
    const int row = wq * 16 + (lane & 7) + ((lane >> 3) & 1) * 8;
    const uint32_t base = tile + row * 128;
    float t0 = 0.f, t1 = 0.f;
#pragma unroll
    for (int kb = 0; kb < 2; kb++) {
        uint32_t x[4][4];
#pragma unroll
        for (int i = 0; i < 4; i++) {
            const int k = K0 + kb * 4 + i, chunk = 2 * k + (lane >> 4);
            asm volatile("ldmatrix.sync.aligned.m8n8.x4.shared.b16 {%0, %1, %2, %3}, [%4];"
                         : "=r"(x[i][0]), "=r"(x[i][1]), "=r"(x[i][2]), "=r"(x[i][3])
                         : "r"(base + (k >> 2) * 8192 + (((chunk & 7) ^ (row & 7)) << 4)));
        }
#pragma unroll
        for (int i = 0; i < 4; i++) {
            float a;
            a = __uint_as_float(x[i][0] << 16); s0 = fmaf(a, a, s0);
            a = __uint_as_float(x[i][0] & 0xffff0000u); t0 = fmaf(a, a, t0);
            a = __uint_as_float(x[i][1] << 16); s1 = fmaf(a, a, s1);
            a = __uint_as_float(x[i][1] & 0xffff0000u); t1 = fmaf(a, a, t1);
            a = __uint_as_float(x[i][2] << 16); s0 = fmaf(a, a, s0);
            a = __uint_as_float(x[i][2] & 0xffff0000u); t0 = fmaf(a, a, t0);
            a = __uint_as_float(x[i][3] << 16); s1 = fmaf(a, a, s1);
            a = __uint_as_float(x[i][3] & 0xffff0000u); t1 = fmaf(a, a, t1);
        }
    }
    s0 += t0;
    s1 += t1;
}
__device__ __forceinline__ void pin_after(float& a, float& b, uint32_t token, uint32_t zero) {
    a = __uint_as_float(__float_as_uint(a) ^ (token & zero));
    b = __uint_as_float(__float_as_uint(b) ^ (token & zero));
}
template <int O>
__device__ __forceinline__ void exp_to_regs(uint32_t (&phi)[64], const float (&a)[64], float qb0, float qb1) {
#pragma unroll
    for (int j = 0; j < 16; j++) {
        phi[O + 2 * j] = pack_bf16(ex2(fmaf(a[4 * j], kC1, qb0)), ex2(fmaf(a[4 * j + 1], kC1, qb0)));
        phi[O + 2 * j + 1] = pack_bf16(ex2(fmaf(a[4 * j + 2], kC1, qb1)), ex2(fmaf(a[4 * j + 3], kC1, qb1)));
    }
}
template <int ID> __device__ __forceinline__ void bar_sync() { asm volatile("bar.sync %0, 256;" :: "n"(ID) : "memory"); }
template <int ID> __device__ __forceinline__ void bar_arrive() { asm volatile("bar.arrive %0, 256;" :: "n"(ID) : "memory"); }

template <int N>
__device__ __forceinline__ void store_out(const float (&o)[N], float inv0, float inv1, __nv_bfloat16* p0) {
#pragma unroll
    for (int t = 0; t < 2; t++) {
#pragma unroll
        for (int i = 0; i < 2; i++) {
            const float inv = i ? inv1 : inv0;
            uint4 v;
            v.x = pack_bf16(o[16 * t + 2 * i] * inv, o[16 * t + 2 * i + 1] * inv);
            v.y = pack_bf16(o[16 * t + 4 + 2 * i] * inv, o[16 * t + 4 + 2 * i + 1] * inv);
            v.z = pack_bf16(o[16 * t + 8 + 2 * i] * inv, o[16 * t + 8 + 2 * i + 1] * inv);
            v.w = pack_bf16(o[16 * t + 12 + 2 * i] * inv, o[16 * t + 12 + 2 * i + 1] * inv);
            *reinterpret_cast<uint4*>(p0 + i * 8 * kDim + t * 32) = v;
        }
    }
}

__global__ void __cluster_dims__(2, 1, 1) __launch_bounds__(384, 1)
performer_kernel(const __grid_constant__ CUtensorMap tm_q, const __grid_constant__ CUtensorMap tm_k,
                 const __grid_constant__ CUtensorMap tm_v, const __grid_constant__ CUtensorMap tm_p,
                 const uint8_t* __restrict__ kptr, const uint8_t* __restrict__ pptr, __nv_bfloat16* __restrict__ out) {
    extern __shared__ __align__(1024) uint8_t smem[];
    const uint32_t sb = (uint32_t)__cvta_generic_to_shared(smem);
    const int tid = threadIdx.x, lane = tid & 31;
    const int warp = __shfl_sync(0xffffffffu, tid >> 5, 0);
    uint32_t rank;
    asm volatile("mov.u32 %0, %%cluster_ctarank;" : "=r"(rank));
    const int cta = blockIdx.x, pair = cta >> 1, h = pair >> 2, sc = pair & 3;

    if (tid == 64) {
        asm volatile("cp.async.bulk.prefetch.L2.global [%0], %1;"
                     :: "l"(kptr + (size_t)(h * kSeq + sc * 512 + rank * 32) * 512), "r"(16384) : "memory");
        asm volatile("cp.async.bulk.prefetch.L2.global [%0], %1;" :: "l"(pptr + cta * 1024), "r"(1024) : "memory");
    }
    if (tid == 32) {
        asm volatile("prefetch.tensormap [%0];" :: "l"(&tm_k) : "memory");
        asm volatile("prefetch.tensormap [%0];" :: "l"(&tm_p) : "memory");
        asm volatile("prefetch.tensormap [%0];" :: "l"(&tm_v) : "memory");
        asm volatile("prefetch.tensormap [%0];" :: "l"(&tm_q) : "memory");
    }
    if (tid == 0) {
        PROF(0);
        mbar_init(bar_addr(sb, B_PROJ), 1);
#pragma unroll
        for (int i = 0; i < 5; i++) { mbar_init(bar_addr(sb, B_FULL + i), 1); mbar_init(bar_addr(sb, B_EMPTY + i), 20); }
#pragma unroll
        for (int i = 0; i < 4; i++) { mbar_init(bar_addr(sb, B_KV + i), 1); mbar_init(bar_addr(sb, B_NORM + i), 1); }
#pragma unroll
        for (int i = 0; i < 2; i++) { mbar_init(bar_addr(sb, B_SFREE + i), 1); mbar_init(bar_addr(sb, B_ACONS + i), 4); }
#pragma unroll
        for (int i = 0; i < 2; i++) mbar_init(bar_addr(sb, B_STG + i), 8);
        mbar_init(bar_addr(sb, B_DUMPED), 1);
        mbar_init(bar_addr(sb, B_PO01), 1);
        mbar_init(bar_addr(sb, B_PO23), 1);
        mbar_init(bar_addr(sb, B_ZERO), 1);
        mbar_init(bar_addr(sb, B_PDEAD), 8);
        mbar_init(bar_addr(sb, B_P0DEAD), 8);
        mbar_init(bar_addr(sb, B_B0DEAD), 4);
        mbar_init(bar_addr(sb, B_KSUM), 1);
        mbar_init(bar_addr(sb, B_GO), 1);
        asm volatile("fence.mbarrier_init.release.cluster;" ::: "memory");
    }
    __syncwarp();
    asm volatile("barrier.cluster.arrive.relaxed.aligned;" ::: "memory");
    asm volatile("barrier.cluster.wait.aligned;" ::: "memory");

    if (warp < 4) {
        reg_dealloc<40>();
        if (warp == 0) {
            if (lane == 0) {
                const int row0 = h * kSeq + sc * 512;
                const uint64_t pol = policy_evict_first();
                auto load_item = [&](int i) {
                    const int s = i % 5;
                    if (i >= 5) mbar_wait(bar_addr(sb, B_EMPTY + s), (i / 5 - 1) & 1);
                    mbar_expect_tx(bar_addr(sb, B_FULL + s), SLOT_BYTES);
                    tma_load_mc(slot_addr(sb, s) + rank * 16384, (i & 1) ? &tm_v : &tm_k, bar_addr(sb, B_FULL + s),
                                row0 + (i >> 1) * 64, rank * 2, pol);
                };
                PROFS(1);
                load_item(0);
                mbar_expect_tx(bar_addr(sb, B_PROJ), 65536);
                tma_load(sb + SM_P0, &tm_p, bar_addr(sb, B_PROJ), rank * 128, 0);
                tma_load(sb + SM_P0 + 32768, &tm_p, bar_addr(sb, B_PROJ), rank * 128, 2);
                load_item(1);
                load_item(2);
                mbar_wait(bar_addr(sb, B_FULL + 0), 0);
                PROFS(3);
                load_item(3);
                mbar_wait(bar_addr(sb, B_FULL + 1), 0);
                load_item(4);
#pragma unroll 1
                for (int i = 5; i < 16; i++) {
                    load_item(i);
                    if (i == 6) mbar_arrive(bar_addr(sb, B_GO));
                }
                CLKP(0);
                const int qrow = row0 + rank * 256;
                auto load_q = [&](int piece, int slot) {
                    mbar_expect_tx(bar_addr(sb, B_FULL + slot), SLOT_BYTES);
                    tma_load_ef(slot_addr(sb, slot), &tm_q, bar_addr(sb, B_FULL + slot), qrow + piece * 64, 0, pol);
                    tma_load_ef(slot_addr(sb, slot) + 16384, &tm_q, bar_addr(sb, B_FULL + slot), qrow + piece * 64, 2, pol);
                };
                mbar_wait(bar_addr(sb, B_EMPTY + 1), 0);
                load_q(0, S_QA);
                mbar_wait(bar_addr(sb, B_EMPTY + 2), 0);
                mbar_expect_tx(bar_addr(sb, B_PO23), SLOT_BYTES);
                tma_load(slot_addr(sb, S_PO23), &tm_p, bar_addr(sb, B_PO23), (rank ^ 1) * 128, 2);
                CLKP(1);
                mbar_wait(bar_addr(sb, B_EMPTY + 3), 0);
                CLKP(3);
                mbar_expect_tx(bar_addr(sb, B_PO01), SLOT_BYTES);
                tma_load(slot_addr(sb, S_PO01), &tm_p, bar_addr(sb, B_PO01), (rank ^ 1) * 128, 0);
                mbar_wait(bar_addr(sb, B_EMPTY + 4), 0);
                load_q(1, S_QB);
                CLKP(4);
                mbar_wait(bar_addr(sb, B_ACONS + 0), 0);
                load_q(2, S_QA);
                CLKP(7);
                mbar_wait(bar_addr(sb, B_ACONS + 1), 0);
                load_q(3, S_QB);
                CLKP(8);
            }
            __syncwarp();
        } else if (warp < 3) {
            const int w = warp - 1;
            const int row = rank * 32 + w * 16 + (lane >> 1);
            int s = 0, ph = 0;
#pragma unroll 1
            for (int t = 0; t < 8; t++) {
                const uint32_t nbar = bar_addr(sb, B_NORM + (t & 3));
                if (w == 0 && lane == 0) mbar_expect_tx(nbar, 256);
                mbar_wait(bar_addr(sb, B_FULL + s), ph);
                const float b = row_bias(slot_addr(sb, s), row, lane & 1);
                if (!(lane & 1)) {
                    const uint32_t dst = sb + SM_NORM + (t & 3) * 256 + row * 4;
                    st_async_f32(dst, b, nbar, 0);
                    st_async_f32(dst, b, nbar, 1);
                }
                __syncwarp();
                if (lane == 0) release_pair(bar_addr(sb, B_EMPTY + s), rank);
                s += 2;
                if (s >= 5) { s -= 5; ph ^= 1; }
            }
            if (w == 0 && lane == 0) {
                const uint32_t src = slot_addr(sb, S_STG);
                mbar_wait(bar_addr(sb, B_ZERO), 0);
#pragma unroll 1
                for (int r = 0; r < 2; r++) {
                    mbar_wait(bar_addr(sb, B_STG + r), 0);
                    CLKP(17 + r);
                    asm volatile("fence.proxy.async.global;" ::: "memory");
                    if (r == 0)
                        asm volatile("cp.reduce.async.bulk.global.shared::cta.bulk_group.add.f32 [%0], [%1], %2;"
                                     :: "l"(g_ksum + h * 256 + rank * 128), "r"(sb + SM_KS), "r"(512) : "memory");
#pragma unroll 1
                    for (int b = 0; b < 8; b++) {
                        const int g2 = b >> 2, u = (b >> 1) & 1, hf = b & 1;
                        uint8_t* dst = reinterpret_cast<uint8_t*>(g_kvacc + h * 8192) + (2 * r + u) * 32768 + (rank * 128 + g2 * 64 + hf * 32) * 128;
                        asm volatile("cp.reduce.async.bulk.global.shared::cta.bulk_group.add.noftz.bf16 [%0], [%1], %2;"
                                     :: "l"(dst), "r"(src + b * 4096), "r"(4096) : "memory");
                        asm volatile("cp.async.bulk.commit_group;" ::: "memory");
                        asm volatile("cp.async.bulk.wait_group.read 0;" ::: "memory");
                    }
                    mbar_arrive(bar_addr(sb, B_SFREE + r));
                    CLKP(9 + r);
                    asm volatile("cp.async.bulk.wait_group 0;" ::: "memory");
                    asm volatile("fence.proxy.async.global;" ::: "memory");
                    red_add_u32(&g_flag_dump[h * 64 + r * 32], 1);
                    if (r == 0) mbar_arrive(bar_addr(sb, B_DUMPED));
                    CLKP(12 + 2 * r);
                }
            }
            __syncwarp();
        } else {
            unsigned target = 0;
            if (lane == 0) target = ld_relaxed_gpu(&g_flag_dump[h * 64 + 32]) + 8;
            mbar_wait(bar_addr(sb, B_GO), 0);
            uint4* z = g_kvacc + h * 8192 + (cta & 7) * 1024;
#pragma unroll 4
            for (int i = 0; i < 32; i++) z[i * 32 + lane] = make_uint4(0, 0, 0, 0);
            g_ksum[h * 256 + (cta & 7) * 32 + lane] = 0.f;
            __syncwarp();
            if (lane == 0) {
                fence_gpu();
                red_add_u32(&g_flag_zero[h * 32], 1);
                spin_flag(&g_flag_zero[h * 32], target);
                asm volatile("fence.proxy.async.global;" ::: "memory");
                mbar_arrive(bar_addr(sb, B_ZERO));
                mbar_wait(bar_addr(sb, B_DUMPED), 0);
                spin_flag(&g_flag_dump[h * 64], target);
                asm volatile("fence.proxy.async.global;" ::: "memory");
                CLKP(15);
            }
            __syncwarp();
            float kv8[8];
#pragma unroll
            for (int i = 0; i < 8; i++) kv8[i] = __ldcg(g_ksum + h * 256 + i * 32 + lane);
            const uint8_t* kvsrc = reinterpret_cast<const uint8_t*>(g_kvacc + h * 8192);
            if (lane == 0) {
                mbar_wait(bar_addr(sb, B_SFREE + 1), 0);
                mbar_expect_tx(bar_addr(sb, B_KV + 0), SLOT_BYTES);
                bulk_load(slot_addr(sb, S_STG), kvsrc, SLOT_BYTES, bar_addr(sb, B_KV + 0));
                mbar_wait(bar_addr(sb, B_P0DEAD), 0);
                mbar_expect_tx(bar_addr(sb, B_KV + 1), SLOT_BYTES);
                bulk_load(sb + SM_P0, kvsrc + 32768, SLOT_BYTES, bar_addr(sb, B_KV + 1));
            }
            __syncwarp();
            if (lane == 0) CLKP(5);
            mbar_wait(bar_addr(sb, B_B0DEAD), 0);
            if (lane == 0) CLKP(6);
#pragma unroll
            for (int i = 0; i < 8; i++) {
                const int m = i * 32 + lane;
                asm volatile("st.shared.v4.u32 [%0], {%1, %1, %1, %1};" :: "r"(slot_addr(sb, S_QA) + m * 128 + ((m & 7) << 4)), "r"(pack_bf16(kv8[i], kv8[i])) : "memory");
            }
            if (lane == 0) CLKP(11);
            asm volatile("fence.proxy.async.shared::cta;" ::: "memory");
            __syncwarp();
            if (lane == 0) {
                mbar_arrive(bar_addr(sb, B_KSUM));
                CLKP(16);
                spin_flag(&g_flag_dump[h * 64 + 32], target);
                asm volatile("fence.proxy.async.global;" ::: "memory");
                mbar_expect_tx(bar_addr(sb, B_KV + 2), SLOT_BYTES);
                bulk_load(sb + SM_P0 + 32768, kvsrc + 65536, SLOT_BYTES, bar_addr(sb, B_KV + 2));
                mbar_wait(bar_addr(sb, B_PDEAD), 0);
                mbar_expect_tx(bar_addr(sb, B_KV + 3), SLOT_BYTES);
                bulk_load(slot_addr(sb, S_PO01), kvsrc + 98304, SLOT_BYTES, bar_addr(sb, B_KV + 3));
            }
            __syncwarp();
        }
        asm volatile("barrier.cluster.arrive.relaxed.aligned;" ::: "memory");
        asm volatile("barrier.cluster.wait.aligned;" ::: "memory");
    } else {
        reg_alloc<232>();
        const int w = (warp - 4) >> 2, wq = warp & 3, g = lane >> 2, c = lane & 3;
        float ks0 = 0.f, ks1 = 0.f, qb0, qb1;
        uint32_t f[64], pk[64];
        auto stage = [&](auto round) {
            constexpr int R = decltype(round)::value;
            const uint32_t stg = slot_addr(sb, S_STG) + w * 16384 + (wq * 16 + g) * 128;
            const bool odd = g & 1;
            const uint32_t o0 = (((odd ? 4 : 0) + c) ^ g) << 4, o1 = (((odd ? 0 : 4) + c) ^ g) << 4;
#pragma unroll
            for (int u = 0; u < 2; u++)
#pragma unroll
                for (int i = 0; i < 2; i++) {
                    const uint32_t* e = pk + 16 * (2 * R + u) + 4 * i;
                    asm volatile("st.shared.v4.u32 [%0], {%1, %2, %3, %4};" :: "r"(stg + u * 8192 + i * 1024 + o0),
                                 "r"(odd ? e[8] : e[0]), "r"(odd ? e[9] : e[1]), "r"(odd ? e[10] : e[2]), "r"(odd ? e[11] : e[3]) : "memory");
                    asm volatile("st.shared.v4.u32 [%0], {%1, %2, %3, %4};" :: "r"(stg + u * 8192 + i * 1024 + o1),
                                 "r"(odd ? e[0] : e[8]), "r"(odd ? e[1] : e[9]), "r"(odd ? e[2] : e[10]), "r"(odd ? e[3] : e[11]) : "memory");
                }
            asm volatile("fence.proxy.async.shared::cta;" ::: "memory");
            __syncwarp();
            if (lane == 0) mbar_arrive(bar_addr(sb, B_STG + R));
        };
        {
            float acc[128];
            uint32_t p[16];
            const uint64_t dp = desc_sw128(sb + SM_P0 + w * 8192, 16);
            mbar_wait(bar_addr(sb, B_PROJ), 0);
            PROFA(0); CLKS(28);
            int ks = 0, kph = 0;
#pragma unroll 1
            for (int t = 0; t < 8; t++) {
                float s[32];
                const int vs = ks == 0 ? 4 : ks - 1, vph = ks == 0 ? kph ^ 1 : kph;
                CLK(0);
                if (w == 1) bar_sync<2>(); else if (t > 0) bar_sync<3>();
                CLK(1);
                if (t > 0) {
                    mbar_wait(bar_addr(sb, B_FULL + vs), vph);
                    const uint64_t dv = desc_sw128(slot_addr(sb, vs), 8192);
                    wg_fence();
#pragma unroll
                    for (int k = 0; k < 4; k++)
                        wgmma_n256_rs_tb(acc, p[4 * k], p[4 * k + 1], p[4 * k + 2], p[4 * k + 3], dv + ((k * 2048) >> 4), (t - 1 + k) > 0);
                    wg_commit();
                }
                CLK(2);
                mbar_wait(bar_addr(sb, B_FULL + ks), kph);
                const uint64_t dk = desc_sw128(slot_addr(sb, ks), 16);
                wg_fence();
#pragma unroll
                for (int k = 0; k < 16; k++)
                    wgmma_n64_ss(s, dp + (((k >> 2) * 16384 + (k & 3) * 32) >> 4), dk + (((k >> 2) * 8192 + (k & 3) * 32) >> 4), k > 0);
                wg_commit();
                if (w == 0) bar_arrive<2>(); else bar_arrive<3>();
                CLK(3);
                if (t > 0) {
                    wg_wait<1>();
                    if (lane == 0) release_pair(bar_addr(sb, B_EMPTY + vs), rank, wq == 0 ? 2 : 1);
                }
                CLK(4);
                wg_wait<0>();
                CLK(5);
                CLKALL(t);
                if (lane == 0) release_pair(bar_addr(sb, B_EMPTY + ks), rank);
                mbar_wait(bar_addr(sb, B_NORM + (t & 3)), (t >> 2) & 1);
                CLK(6);
                const uint32_t nb = sb + SM_NORM + (t & 3) * 256 + c * 8;
                float bias[16];
#pragma unroll
                for (int j = 0; j < 8; j++)
                    asm volatile("ld.shared.v2.f32 {%0, %1}, [%2];" : "=f"(bias[2 * j]), "=f"(bias[2 * j + 1]) : "r"(nb + j * 32) : "memory");
#pragma unroll
                for (int j = 0; j < 8; j++) {
                    const float bx = bias[2 * j], by = bias[2 * j + 1];
                    const float p00 = ex2(fmaf(s[4 * j], kC1, bx)), p01 = ex2(fmaf(s[4 * j + 1], kC1, by));
                    const float p10 = ex2(fmaf(s[4 * j + 2], kC1, bx)), p11 = ex2(fmaf(s[4 * j + 3], kC1, by));
                    ks0 += p00 + p01;
                    ks1 += p10 + p11;
                    p[2 * j] = pack_bf16(p00, p01);
                    p[2 * j + 1] = pack_bf16(p10, p11);
                }
                CLK(7);
                ks += 2;
                if (ks >= 5) { ks -= 5; kph ^= 1; }
            }
            if (w == 1) bar_sync<2>(); else bar_sync<3>();
            mbar_wait(bar_addr(sb, B_FULL + 0), 1);
            {
                const uint64_t dv = desc_sw128(slot_addr(sb, 0), 8192);
                wg_fence();
#pragma unroll
                for (int k = 0; k < 4; k++)
                    wgmma_n256_rs_tb(acc, p[4 * k], p[4 * k + 1], p[4 * k + 2], p[4 * k + 3], dv + ((k * 2048) >> 4), 1);
                wg_commit();
            }
            if (w == 0) bar_arrive<2>();
            wg_wait<0>();
            PROFA(6); CLKS(11);
            ks0 += __shfl_xor_sync(0xffffffffu, ks0, 1); ks0 += __shfl_xor_sync(0xffffffffu, ks0, 2);
            ks1 += __shfl_xor_sync(0xffffffffu, ks1, 1); ks1 += __shfl_xor_sync(0xffffffffu, ks1, 2);
            if (c == 0) {
                asm volatile("st.shared.f32 [%0], %1;" :: "r"(sb + SM_KS + (w * 64 + wq * 16 + g) * 4), "f"(ks0) : "memory");
                asm volatile("st.shared.f32 [%0], %1;" :: "r"(sb + SM_KS + (w * 64 + wq * 16 + g + 8) * 4), "f"(ks1) : "memory");
            }
#pragma unroll
            for (int t = 0; t < 8; t++)
#pragma unroll
                for (int i = 0; i < 2; i++)
#pragma unroll
                    for (int jj = 0; jj < 4; jj++)
                        pk[8 * t + 4 * i + jj] = pack_bf16(acc[16 * t + 4 * jj + 2 * i], acc[16 * t + 4 * jj + 2 * i + 1]);
            auto load_a = [&]() {
                mbar_wait(bar_addr(sb, B_FULL + (w == 0 ? S_QA : S_QB)), 1);
                PROFW(8); CLKS(13);
                load_q_frags(f, qb0, qb1, slot_addr(sb, w == 0 ? S_QA : S_QB), wq, lane);
                asm volatile("fence.proxy.async.shared::cta;" ::: "memory");
                __syncwarp();
                if (lane == 0) mbar_arrive(bar_addr(sb, B_ACONS + w));
            };
            bar_sync<3>();
            stage(Int<0>{});
            PROFW(7); CLKS(12);
            load_a();
            PROFW(9); CLKS(14);
        }

        uint32_t phi[64], phib[64];
        const uint32_t qsb = slot_addr(sb, w == 0 ? S_QA : S_QB);
        {
            const uint32_t p0 = sb + SM_P0, po01 = slot_addr(sb, S_PO01), po23 = slot_addr(sb, S_PO23);
            float a[64];
            gemm3(a, f, p0, p0 + 32768);
            PROFW(10); CLKS(15);
            wg_wait<0>();
            PROFW(11); CLKS(16);
            exp_to_regs<0>(phi, a, qb0, qb1);
            PROFW(12); CLKS(17);
            if (w == 1) {
                mbar_wait(bar_addr(sb, B_SFREE + 0), 0);
                stage(Int<1>{});
            }
            mbar_wait(bar_addr(sb, B_PO01), 0);
            mbar_wait(bar_addr(sb, B_PO23), 0);
            PROFW(13); CLKS(18);
            gemm3(a, f, po01, po23);
            PROFW(14); CLKS(19);
            if (w == 0) {
                mbar_wait(bar_addr(sb, B_SFREE + 0), 0);
                stage(Int<1>{});
            }
            wg_wait<0>();
            PROFW(16); CLKS(20);
            exp_to_regs<32>(phi, a, qb0, qb1);
            mbar_wait(bar_addr(sb, B_FULL + (w == 0 ? S_QA : S_QB)), 0);
            PROFW(17); CLKS(21);
            float s0 = 0.f, s1 = 0.f;
            wg_fence();
            gemm3_ss<0>(a, qsb, p0);
            tile_sumsq<0>(s0, s1, qsb, wq, lane);
            gemm3_ss<8>(a, qsb, p0 + 32768);
            wg_commit();
            tile_sumsq<8>(s0, s1, qsb, wq, lane);
            s0 += __shfl_xor_sync(0xffffffffu, s0, 1); s1 += __shfl_xor_sync(0xffffffffu, s1, 1);
            s0 += __shfl_xor_sync(0xffffffffu, s0, 2); s1 += __shfl_xor_sync(0xffffffffu, s1, 2);
            qb0 = fmaf(s0, kC2, kC3);
            qb1 = fmaf(s1, kC2, kC3);
            PROFW(18); CLKS(22);
            wg_wait<0>();
            PROFW(19); CLKS(23);
            pin_after(qb0, qb1, mbar_arrive_lane0(bar_addr(sb, B_P0DEAD), lane), rank >> 8);
            exp_to_regs<0>(phib, a, qb0, qb1);
            wg_fence();
            gemm3_ss<0>(a, qsb, po01);
            gemm3_ss<8>(a, qsb, po23);
            wg_commit();
            wg_wait<0>();
            PROFW(21); CLKS(24);
            if (w == 0 && lane == 0) mbar_arrive(bar_addr(sb, B_B0DEAD));
            pin_after(qb0, qb1, mbar_arrive_lane0(bar_addr(sb, B_PDEAD), lane), rank >> 8);
            exp_to_regs<32>(phib, a, qb0, qb1);
            PROFW(22); CLKS(25);
        }
        asm volatile("barrier.cluster.arrive.relaxed.aligned;" ::: "memory");
        {
            const uint32_t kvb[4] = {slot_addr(sb, S_STG), sb + SM_P0, sb + SM_P0 + 32768, slot_addr(sb, S_PO01)};
            const uint32_t mo = rank * 128 * 128, mx = (rank ^ 1) * 128 * 128;
            const int orow = h * kSeq + sc * 512 + rank * 256 + w * 64 + wq * 16 + g;
            __nv_bfloat16* pA = out + (size_t)orow * kDim + c * 8;
            __nv_bfloat16* pB = pA + 128 * kDim;
            float iA0, iA1, iB0, iB1;
            auto take_turn = [&](bool first) { if (w == 1) bar_sync<2>(); else if (!first) bar_sync<3>(); };
            auto give_turn = [&](bool last) { if (w == 0) bar_arrive<2>(); else if (!last) bar_arrive<3>(); };
            {
                float e[36];
                const uint32_t lbo = slot_addr(sb, S_QA) - slot_addr(sb, S_STG);
                auto tile0 = [&](const uint32_t (&ph)[64], bool first) {
                    const uint64_t d0 = desc_sw128(kvb[0] + mo, lbo), d1 = desc_sw128(kvb[0] + mx, lbo);
                    take_turn(first);
                    wg_fence();
#pragma unroll
                    for (int k = 0; k < 16; k++)
                        wgmma_n72_rs_tb(e, ph[4 * k], ph[4 * k + 1], ph[4 * k + 2], ph[4 * k + 3], (k < 8 ? d0 : d1) + (((k & 7) * 2048) >> 4), k > 0);
                    wg_commit();
                    give_turn(false);
                    wg_wait<0>();
                };
                mbar_wait(bar_addr(sb, B_KV + 0), 0);
                mbar_wait(bar_addr(sb, B_KSUM), 0);
                PROFA(23); CLKS(26);
                tile0(phi, true);
                iA0 = __fdividef(1.f, e[32] + 1e-6f);
                iA1 = __fdividef(1.f, e[34] + 1e-6f);
                store_out(e, iA0, iA1, pA);
                CLKG4(0);
                tile0(phib, false);
                iB0 = __fdividef(1.f, e[32] + 1e-6f);
                iB1 = __fdividef(1.f, e[34] + 1e-6f);
                store_out(e, iB0, iB1, pB);
                CLKG4(1);
            }
#pragma unroll
            for (int i = 2; i < 8; i++) {
                const int b = i >> 1;
                float o[32];
                const uint64_t d0 = desc_sw128(kvb[b] + mo, 16), d1 = desc_sw128(kvb[b] + mx, 16);
                if (!(i & 1)) mbar_wait(bar_addr(sb, B_KV + b), 0);
                take_turn(false);
                wg_fence();
#pragma unroll
                for (int k = 0; k < 16; k++) {
                    const uint32_t (&ph)[64] = (i & 1) ? phib : phi;
                    wgmma_n64_rs_tb(o, ph[4 * k], ph[4 * k + 1], ph[4 * k + 2], ph[4 * k + 3], (k < 8 ? d0 : d1) + (((k & 7) * 2048) >> 4), k > 0);
                }
                wg_commit();
                give_turn(i == 7);
                wg_wait<0>();
                if (i & 1) store_out(o, iB0, iB1, pB + b * 64); else store_out(o, iA0, iA1, pA + b * 64);
                CLKG4(i);
            }
        }
        PROFA(24);
        CLKS(27);
        asm volatile("barrier.cluster.wait.aligned;" ::: "memory");
    }
}

typedef CUresult (*EncodeTiledFn)(CUtensorMap*, CUtensorMapDataType, cuuint32_t, void*, const cuuint64_t*, const cuuint64_t*,
                                  const cuuint32_t*, const cuuint32_t*, CUtensorMapInterleave, CUtensorMapSwizzle,
                                  CUtensorMapL2promotion, CUtensorMapFloatOOBfill);

bool make_map(EncodeTiledFn enc, CUtensorMap* m, const void* base, uint64_t rows, uint32_t box_rows) {
    cuuint64_t dims[3] = {64, rows, 4};
    cuuint64_t strides[2] = {512, 128};
    cuuint32_t box[3] = {64, box_rows, 2};
    cuuint32_t es[3] = {1, 1, 1};
    return enc(m, CU_TENSOR_MAP_DATA_TYPE_BFLOAT16, 3, const_cast<void*>(base), dims, strides, box, es,
               CU_TENSOR_MAP_INTERLEAVE_NONE, CU_TENSOR_MAP_SWIZZLE_128B, CU_TENSOR_MAP_L2_PROMOTION_L2_256B,
               CU_TENSOR_MAP_FLOAT_OOB_FILL_NONE) == CUDA_SUCCESS;
}

}

extern "C" void kernel_launch(void* const* d_in, const int* in_sizes, int n_in, void* d_out, int out_size) {
    (void)in_sizes; (void)n_in; (void)out_size;
    static EncodeTiledFn enc = nullptr;
    if (!enc) {
        void* fn = nullptr;
        cudaDriverEntryPointQueryResult qr;
        if (cudaGetDriverEntryPoint("cuTensorMapEncodeTiled", &fn, cudaEnableDefault, &qr) != cudaSuccess || !fn) return;
        enc = (EncodeTiledFn)fn;
        cudaFuncSetAttribute(performer_kernel, cudaFuncAttributeMaxDynamicSharedMemorySize, SM_TOTAL);
    }
    CUtensorMap tq, tk, tv, tp;
    if (!make_map(enc, &tq, d_in[0], kHeads * kSeq, 64) || !make_map(enc, &tk, d_in[1], kHeads * kSeq, 64) ||
        !make_map(enc, &tv, d_in[2], kHeads * kSeq, 64) || !make_map(enc, &tp, d_in[3], 256, 128)) return;
    performer_kernel<<<128, 384, SM_TOTAL, cudaStreamPerThread>>>(tq, tk, tv, tp, (const uint8_t*)d_in[1], (const uint8_t*)d_in[3],
                                                                    (__nv_bfloat16*)d_out);
}
```

```cpp
#include <cuda_runtime.h>
#include <cuda_bf16.h>
#include <cuda.h>
#include <stdint.h>

namespace {

constexpr int kHeads = 16;
constexpr int kSeq = 2048;
constexpr int kDim = 256;

constexpr uint32_t SM_P0 = 0;
constexpr uint32_t SM_SLOT = 65536;
constexpr uint32_t SLOT_BYTES = 32768;
constexpr uint32_t SM_BAR = SM_SLOT + 5 * SLOT_BYTES;
constexpr uint32_t SM_NORM = SM_BAR + 512;
constexpr uint32_t SM_KS = SM_NORM + 1024;
constexpr uint32_t SM_TOTAL = SM_KS + 512;

constexpr int S_STG = 0, S_QA = 1, S_PO23 = 2, S_PO01 = 3, S_QB = 4;

constexpr int B_PROJ = 0;
constexpr int B_FULL = 1;
constexpr int B_EMPTY = 6;
constexpr int B_NORM = 11;
constexpr int B_KV = 15;
constexpr int B_STG = 19;
constexpr int B_GO = 21;
constexpr int B_ACONS = 22;
constexpr int B_SFREE = 24;
constexpr int B_PO01 = 26;
constexpr int B_PO23 = 27;
constexpr int B_ZERO = 28;
constexpr int B_PDEAD = 29;
constexpr int B_B0DEAD = 30;
constexpr int B_KSUM = 31;
constexpr int B_DUMPED = 32;
constexpr int B_P0DEAD = 33;

constexpr int kG1Rs = 7;
constexpr int kSpinLimit = 1 << 21;

__device__ uint4 g_kvacc[kHeads * 8192];
__device__ float g_ksum[kHeads * 256];
__device__ unsigned g_flag_zero[kHeads * 32];
__device__ unsigned g_flag_dump[kHeads * 64];
#define PROF(i) do {} while (0)
#define PROFW(i) do {} while (0)
#define PROFA(i) do {} while (0)
#define PROFS(i) do {} while (0)
#define CLK(i) do {} while (0)
#define CLKS(i) do {} while (0)
#define CLKP(i) do {} while (0)
#define CLKALL(i) do {} while (0)
#define CLKG4(i) do {} while (0)

__device__ __forceinline__ void mbar_init(uint32_t bar, uint32_t cnt) {
    asm volatile("mbarrier.init.shared::cta.b64 [%0], %1;" :: "r"(bar), "r"(cnt) : "memory");
}
__device__ __forceinline__ void mbar_expect_tx(uint32_t bar, uint32_t bytes) {
    asm volatile("mbarrier.arrive.expect_tx.shared::cta.b64 _, [%0], %1;" :: "r"(bar), "r"(bytes) : "memory");
}
__device__ __forceinline__ void mbar_arrive(uint32_t bar) {
    asm volatile("mbarrier.arrive.shared::cta.b64 _, [%0];" :: "r"(bar) : "memory");
}
__device__ __forceinline__ uint32_t mbar_arrive_lane0(uint32_t bar, int lane) {
    uint32_t lo;
    asm volatile("{\n.reg .pred p;\n.reg .b64 st;\n.reg .b32 hi;\nmov.b64 st, 0;\nsetp.eq.s32 p, %2, 0;\n"
                 "@p mbarrier.arrive.shared::cta.b64 st, [%1];\nmov.b64 {%0, hi}, st;\n}" : "=r"(lo) : "r"(bar), "r"(lane) : "memory");
    return lo;
}
__device__ __forceinline__ void mbar_arrive_n(uint32_t bar, uint32_t cta, uint32_t count) {
    asm volatile("{\n.reg .b32 ra;\nmapa.shared::cluster.u32 ra, %0, %1;\n"
                 "mbarrier.arrive.shared::cluster.b64 _, [ra], %2;\n}" :: "r"(bar), "r"(cta), "r"(count) : "memory");
}
__device__ __forceinline__ void mbar_wait(uint32_t bar, uint32_t parity) {
    uint32_t ok;
    int it = 0;
    do {
        asm volatile("{\n.reg .pred p;\nmbarrier.try_wait.parity.shared::cta.b64 p, [%1], %2;\nselp.u32 %0, 1, 0, p;\n}"
                     : "=r"(ok) : "r"(bar), "r"(parity) : "memory");
    } while (!ok && ++it < kSpinLimit);
}
__device__ __forceinline__ void tma_load(uint32_t dst, const CUtensorMap* tm, uint32_t bar, int row, int blk) {
    asm volatile("cp.async.bulk.tensor.3d.shared::cluster.global.mbarrier::complete_tx::bytes [%0], [%1, {%3, %4, %5}], [%2];"
                 :: "r"(dst), "l"(tm), "r"(bar), "r"(0), "r"(row), "r"(blk) : "memory");
}
__device__ __forceinline__ uint64_t policy_evict_first() {
    uint64_t p;
    asm volatile("createpolicy.fractional.L2::evict_first.b64 %0, 1.0;" : "=l"(p));
    return p;
}
__device__ __forceinline__ void tma_load_ef(uint32_t dst, const CUtensorMap* tm, uint32_t bar, int row, int blk, uint64_t pol) {
    asm volatile("cp.async.bulk.tensor.3d.shared::cluster.global.mbarrier::complete_tx::bytes.L2::cache_hint [%0], [%1, {%3, %4, %5}], [%2], %6;"
                 :: "r"(dst), "l"(tm), "r"(bar), "r"(0), "r"(row), "r"(blk), "l"(pol) : "memory");
}
__device__ __forceinline__ void tma_load_mc(uint32_t dst, const CUtensorMap* tm, uint32_t bar, int row, int blk, uint64_t pol) {
    asm volatile("cp.async.bulk.tensor.3d.shared::cluster.global.mbarrier::complete_tx::bytes.multicast::cluster.L2::cache_hint [%0], [%1, {%3, %4, %5}], [%2], %6, %7;"
                 :: "r"(dst), "l"(tm), "r"(bar), "r"(0), "r"(row), "r"(blk), "h"((uint16_t)3), "l"(pol) : "memory");
}
__device__ __forceinline__ void bulk_load(uint32_t dst, const void* src, uint32_t bytes, uint32_t bar) {
    asm volatile("cp.async.bulk.shared::cluster.global.mbarrier::complete_tx::bytes [%0], [%1], %2, [%3];"
                 :: "r"(dst), "l"(src), "r"(bytes), "r"(bar) : "memory");
}
__device__ __forceinline__ void wg_fence() { asm volatile("wgmma.fence.sync.aligned;" ::: "memory"); }
__device__ __forceinline__ void wg_commit() { asm volatile("wgmma.commit_group.sync.aligned;" ::: "memory"); }
template <int N> __device__ __forceinline__ void wg_wait() { asm volatile("wgmma.wait_group.sync.aligned %0;" :: "n"(N) : "memory"); }

__device__ __forceinline__ uint64_t desc_sw128(uint32_t addr, uint32_t lbo) {
    asm volatile("" : "+r"(addr));
    return (uint64_t)((addr & 0x3FFFF) >> 4) | ((uint64_t)(lbo >> 4) << 16) | ((uint64_t)(1024 >> 4) << 32) | (1ull << 62);
}
__device__ __forceinline__ uint32_t pack_bf16(float lo, float hi) {
    uint32_t r;
    asm("cvt.rn.bf16x2.f32 %0, %1, %2;" : "=r"(r) : "f"(hi), "f"(lo));
    return r;
}
__device__ __forceinline__ float ex2(float x) {
    float y;
    asm("ex2.approx.ftz.f32 %0, %1;" : "=f"(y) : "f"(x));
    return y;
}
__device__ __forceinline__ unsigned ld_relaxed_gpu(const unsigned* p) {
    unsigned v;
    asm volatile("ld.relaxed.gpu.global.u32 %0, [%1];" : "=r"(v) : "l"(p) : "memory");
    return v;
}
__device__ __forceinline__ void fence_gpu() { asm volatile("fence.acq_rel.gpu;" ::: "memory"); }
__device__ __forceinline__ void red_add_u32(unsigned* p, unsigned v) {
    asm volatile("red.relaxed.gpu.global.add.u32 [%0], %1;" :: "l"(p), "r"(v) : "memory");
}
__device__ __forceinline__ unsigned ld_acquire_gpu(const unsigned* p) {
    unsigned v;
    asm volatile("ld.acquire.gpu.global.u32 %0, [%1];" : "=r"(v) : "l"(p) : "memory");
    return v;
}
__device__ __forceinline__ void spin_flag(const unsigned* p, unsigned target) {
    int it = 0;
    while ((int)(ld_acquire_gpu(p) - target) < 0 && ++it < kSpinLimit) {}
}
template <int R> __device__ __forceinline__ void reg_alloc() { asm volatile("setmaxnreg.inc.sync.aligned.u32 %0;" :: "n"(R)); }
template <int R> __device__ __forceinline__ void reg_dealloc() { asm volatile("setmaxnreg.dec.sync.aligned.u32 %0;" :: "n"(R)); }

template <int N>
__device__ __forceinline__ void wgmma_n64_ss(float (&d)[N], uint64_t da, uint64_t db, int scale_d) {
    asm volatile("{\n.reg .pred p;\nsetp.ne.b32 p, %34, 0;\n"
        "wgmma.mma_async.sync.aligned.m64n64k16.f32.bf16.bf16 "
        "{%0, %1, %2, %3, %4, %5, %6, %7, %8, %9, %10, %11, %12, %13, %14, %15, "
        "%16, %17, %18, %19, %20, %21, %22, %23, %24, %25, %26, %27, %28, %29, %30, %31}, "
        "%32, %33, p, 1, 1, 0, 0;\n}\n"
        : "+f"(d[0]), "+f"(d[1]), "+f"(d[2]), "+f"(d[3]), "+f"(d[4]), "+f"(d[5]), "+f"(d[6]), "+f"(d[7]),
          "+f"(d[8]), "+f"(d[9]), "+f"(d[10]), "+f"(d[11]), "+f"(d[12]), "+f"(d[13]), "+f"(d[14]), "+f"(d[15]),
          "+f"(d[16]), "+f"(d[17]), "+f"(d[18]), "+f"(d[19]), "+f"(d[20]), "+f"(d[21]), "+f"(d[22]), "+f"(d[23]),
          "+f"(d[24]), "+f"(d[25]), "+f"(d[26]), "+f"(d[27]), "+f"(d[28]), "+f"(d[29]), "+f"(d[30]), "+f"(d[31])
        : "l"(da), "l"(db), "r"(scale_d));
}
template <int N>
__device__ __forceinline__ void wgmma_n64_rs(float (&d)[N], uint32_t a0, uint32_t a1, uint32_t a2, uint32_t a3, uint64_t db, int scale_d) {
    asm volatile("{\n.reg .pred p;\nsetp.ne.b32 p, %37, 0;\n"
        "wgmma.mma_async.sync.aligned.m64n64k16.f32.bf16.bf16 "
        "{%0, %1, %2, %3, %4, %5, %6, %7, %8, %9, %10, %11, %12, %13, %14, %15, "
        "%16, %17, %18, %19, %20, %21, %22, %23, %24, %25, %26, %27, %28, %29, %30, %31}, "
        "{%32, %33, %34, %35}, %36, p, 1, 1, 0;\n}\n"
        : "+f"(d[0]), "+f"(d[1]), "+f"(d[2]), "+f"(d[3]), "+f"(d[4]), "+f"(d[5]), "+f"(d[6]), "+f"(d[7]),
          "+f"(d[8]), "+f"(d[9]), "+f"(d[10]), "+f"(d[11]), "+f"(d[12]), "+f"(d[13]), "+f"(d[14]), "+f"(d[15]),
          "+f"(d[16]), "+f"(d[17]), "+f"(d[18]), "+f"(d[19]), "+f"(d[20]), "+f"(d[21]), "+f"(d[22]), "+f"(d[23]),
          "+f"(d[24]), "+f"(d[25]), "+f"(d[26]), "+f"(d[27]), "+f"(d[28]), "+f"(d[29]), "+f"(d[30]), "+f"(d[31])
        : "r"(a0), "r"(a1), "r"(a2), "r"(a3), "l"(db), "r"(scale_d));
}
template <int N>
__device__ __forceinline__ void wgmma_n64_rs_tb(float (&d)[N], uint32_t a0, uint32_t a1, uint32_t a2, uint32_t a3, uint64_t db, int scale_d) {
    asm volatile("{\n.reg .pred p;\nsetp.ne.b32 p, %37, 0;\n"
        "wgmma.mma_async.sync.aligned.m64n64k16.f32.bf16.bf16 "
        "{%0, %1, %2, %3, %4, %5, %6, %7, %8, %9, %10, %11, %12, %13, %14, %15, "
        "%16, %17, %18, %19, %20, %21, %22, %23, %24, %25, %26, %27, %28, %29, %30, %31}, "
        "{%32, %33, %34, %35}, %36, p, 1, 1, 1;\n}\n"
        : "+f"(d[0]), "+f"(d[1]), "+f"(d[2]), "+f"(d[3]), "+f"(d[4]), "+f"(d[5]), "+f"(d[6]), "+f"(d[7]),
          "+f"(d[8]), "+f"(d[9]), "+f"(d[10]), "+f"(d[11]), "+f"(d[12]), "+f"(d[13]), "+f"(d[14]), "+f"(d[15]),
          "+f"(d[16]), "+f"(d[17]), "+f"(d[18]), "+f"(d[19]), "+f"(d[20]), "+f"(d[21]), "+f"(d[22]), "+f"(d[23]),
          "+f"(d[24]), "+f"(d[25]), "+f"(d[26]), "+f"(d[27]), "+f"(d[28]), "+f"(d[29]), "+f"(d[30]), "+f"(d[31])
        : "r"(a0), "r"(a1), "r"(a2), "r"(a3), "l"(db), "r"(scale_d));
}
template <int N>
__device__ __forceinline__ void wgmma_n72_rs_tb(float (&d)[N], uint32_t a0, uint32_t a1, uint32_t a2, uint32_t a3, uint64_t db, int scale_d) {
    asm volatile("{\n.reg .pred p;\nsetp.ne.b32 p, %41, 0;\n"
        "wgmma.mma_async.sync.aligned.m64n72k16.f32.bf16.bf16 "
        "{%0, %1, %2, %3, %4, %5, %6, %7, %8, %9, %10, %11, %12, %13, %14, %15, "
        "%16, %17, %18, %19, %20, %21, %22, %23, %24, %25, %26, %27, %28, %29, %30, %31, "
        "%32, %33, %34, %35}, "
        "{%36, %37, %38, %39}, %40, p, 1, 1, 1;\n}\n"
        : "+f"(d[0]), "+f"(d[1]), "+f"(d[2]), "+f"(d[3]), "+f"(d[4]), "+f"(d[5]), "+f"(d[6]), "+f"(d[7]),
          "+f"(d[8]), "+f"(d[9]), "+f"(d[10]), "+f"(d[11]), "+f"(d[12]), "+f"(d[13]), "+f"(d[14]), "+f"(d[15]),
          "+f"(d[16]), "+f"(d[17]), "+f"(d[18]), "+f"(d[19]), "+f"(d[20]), "+f"(d[21]), "+f"(d[22]), "+f"(d[23]),
          "+f"(d[24]), "+f"(d[25]), "+f"(d[26]), "+f"(d[27]), "+f"(d[28]), "+f"(d[29]), "+f"(d[30]), "+f"(d[31]),
          "+f"(d[32]), "+f"(d[33]), "+f"(d[34]), "+f"(d[35])
        : "r"(a0), "r"(a1), "r"(a2), "r"(a3), "l"(db), "r"(scale_d));
}
template <int N>
__device__ __forceinline__ void wgmma_n128_rs(float (&d)[N], uint32_t a0, uint32_t a1, uint32_t a2, uint32_t a3, uint64_t db, int scale_d) {
    asm volatile("{\n.reg .pred p;\nsetp.ne.b32 p, %69, 0;\n"
        "wgmma.mma_async.sync.aligned.m64n128k16.f32.bf16.bf16 "
        "{%0, %1, %2, %3, %4, %5, %6, %7, %8, %9, %10, %11, %12, %13, %14, %15, "
        "%16, %17, %18, %19, %20, %21, %22, %23, %24, %25, %26, %27, %28, %29, %30, %31, "
        "%32, %33, %34, %35, %36, %37, %38, %39, %40, %41, %42, %43, %44, %45, %46, %47, "
        "%48, %49, %50, %51, %52, %53, %54, %55, %56, %57, %58, %59, %60, %61, %62, %63}, "
        "{%64, %65, %66, %67}, %68, p, 1, 1, 0;\n}\n"
        : "+f"(d[0]), "+f"(d[1]), "+f"(d[2]), "+f"(d[3]), "+f"(d[4]), "+f"(d[5]), "+f"(d[6]), "+f"(d[7]),
          "+f"(d[8]), "+f"(d[9]), "+f"(d[10]), "+f"(d[11]), "+f"(d[12]), "+f"(d[13]), "+f"(d[14]), "+f"(d[15]),
          "+f"(d[16]), "+f"(d[17]), "+f"(d[18]), "+f"(d[19]), "+f"(d[20]), "+f"(d[21]), "+f"(d[22]), "+f"(d[23]),
          "+f"(d[24]), "+f"(d[25]), "+f"(d[26]), "+f"(d[27]), "+f"(d[28]), "+f"(d[29]), "+f"(d[30]), "+f"(d[31]),
          "+f"(d[32]), "+f"(d[33]), "+f"(d[34]), "+f"(d[35]), "+f"(d[36]), "+f"(d[37]), "+f"(d[38]), "+f"(d[39]),
          "+f"(d[40]), "+f"(d[41]), "+f"(d[42]), "+f"(d[43]), "+f"(d[44]), "+f"(d[45]), "+f"(d[46]), "+f"(d[47]),
          "+f"(d[48]), "+f"(d[49]), "+f"(d[50]), "+f"(d[51]), "+f"(d[52]), "+f"(d[53]), "+f"(d[54]), "+f"(d[55]),
          "+f"(d[56]), "+f"(d[57]), "+f"(d[58]), "+f"(d[59]), "+f"(d[60]), "+f"(d[61]), "+f"(d[62]), "+f"(d[63])
        : "r"(a0), "r"(a1), "r"(a2), "r"(a3), "l"(db), "r"(scale_d));
}
template <int N>
__device__ __forceinline__ void wgmma_n128_ss(float (&d)[N], uint64_t da, uint64_t db, int scale_d) {
    asm volatile("{\n.reg .pred p;\nsetp.ne.b32 p, %66, 0;\n"
        "wgmma.mma_async.sync.aligned.m64n128k16.f32.bf16.bf16 "
        "{%0, %1, %2, %3, %4, %5, %6, %7, %8, %9, %10, %11, %12, %13, %14, %15, "
        "%16, %17, %18, %19, %20, %21, %22, %23, %24, %25, %26, %27, %28, %29, %30, %31, "
        "%32, %33, %34, %35, %36, %37, %38, %39, %40, %41, %42, %43, %44, %45, %46, %47, "
        "%48, %49, %50, %51, %52, %53, %54, %55, %56, %57, %58, %59, %60, %61, %62, %63}, "
        "%64, %65, p, 1, 1, 0, 0;\n}\n"
        : "+f"(d[0]), "+f"(d[1]), "+f"(d[2]), "+f"(d[3]), "+f"(d[4]), "+f"(d[5]), "+f"(d[6]), "+f"(d[7]),
          "+f"(d[8]), "+f"(d[9]), "+f"(d[10]), "+f"(d[11]), "+f"(d[12]), "+f"(d[13]), "+f"(d[14]), "+f"(d[15]),
          "+f"(d[16]), "+f"(d[17]), "+f"(d[18]), "+f"(d[19]), "+f"(d[20]), "+f"(d[21]), "+f"(d[22]), "+f"(d[23]),
          "+f"(d[24]), "+f"(d[25]), "+f"(d[26]), "+f"(d[27]), "+f"(d[28]), "+f"(d[29]), "+f"(d[30]), "+f"(d[31]),
          "+f"(d[32]), "+f"(d[33]), "+f"(d[34]), "+f"(d[35]), "+f"(d[36]), "+f"(d[37]), "+f"(d[38]), "+f"(d[39]),
          "+f"(d[40]), "+f"(d[41]), "+f"(d[42]), "+f"(d[43]), "+f"(d[44]), "+f"(d[45]), "+f"(d[46]), "+f"(d[47]),
          "+f"(d[48]), "+f"(d[49]), "+f"(d[50]), "+f"(d[51]), "+f"(d[52]), "+f"(d[53]), "+f"(d[54]), "+f"(d[55]),
          "+f"(d[56]), "+f"(d[57]), "+f"(d[58]), "+f"(d[59]), "+f"(d[60]), "+f"(d[61]), "+f"(d[62]), "+f"(d[63])
        : "l"(da), "l"(db), "r"(scale_d));
}
template <int N>
__device__ __forceinline__ void wgmma_n256_rs_tb(float (&d)[N], uint32_t a0, uint32_t a1, uint32_t a2, uint32_t a3, uint64_t db, int scale_d) {
    asm volatile("{\n.reg .pred p;\nsetp.ne.b32 p, %133, 0;\n"
        "wgmma.mma_async.sync.aligned.m64n256k16.f32.bf16.bf16 "
        "{%0, %1, %2, %3, %4, %5, %6, %7, %8, %9, %10, %11, %12, %13, %14, %15, "
        "%16, %17, %18, %19, %20, %21, %22, %23, %24, %25, %26, %27, %28, %29, %30, %31, "
        "%32, %33, %34, %35, %36, %37, %38, %39, %40, %41, %42, %43, %44, %45, %46, %47, "
        "%48, %49, %50, %51, %52, %53, %54, %55, %56, %57, %58, %59, %60, %61, %62, %63, "
        "%64, %65, %66, %67, %68, %69, %70, %71, %72, %73, %74, %75, %76, %77, %78, %79, "
        "%80, %81, %82, %83, %84, %85, %86, %87, %88, %89, %90, %91, %92, %93, %94, %95, "
        "%96, %97, %98, %99, %100, %101, %102, %103, %104, %105, %106, %107, %108, %109, %110, %111, "
        "%112, %113, %114, %115, %116, %117, %118, %119, %120, %121, %122, %123, %124, %125, %126, %127}, "
        "{%128, %129, %130, %131}, %132, p, 1, 1, 1;\n}\n"
        : "+f"(d[0]), "+f"(d[1]), "+f"(d[2]), "+f"(d[3]), "+f"(d[4]), "+f"(d[5]), "+f"(d[6]), "+f"(d[7]),
          "+f"(d[8]), "+f"(d[9]), "+f"(d[10]), "+f"(d[11]), "+f"(d[12]), "+f"(d[13]), "+f"(d[14]), "+f"(d[15]),
          "+f"(d[16]), "+f"(d[17]), "+f"(d[18]), "+f"(d[19]), "+f"(d[20]), "+f"(d[21]), "+f"(d[22]), "+f"(d[23]),
          "+f"(d[24]), "+f"(d[25]), "+f"(d[26]), "+f"(d[27]), "+f"(d[28]), "+f"(d[29]), "+f"(d[30]), "+f"(d[31]),
          "+f"(d[32]), "+f"(d[33]), "+f"(d[34]), "+f"(d[35]), "+f"(d[36]), "+f"(d[37]), "+f"(d[38]), "+f"(d[39]),
          "+f"(d[40]), "+f"(d[41]), "+f"(d[42]), "+f"(d[43]), "+f"(d[44]), "+f"(d[45]), "+f"(d[46]), "+f"(d[47]),
          "+f"(d[48]), "+f"(d[49]), "+f"(d[50]), "+f"(d[51]), "+f"(d[52]), "+f"(d[53]), "+f"(d[54]), "+f"(d[55]),
          "+f"(d[56]), "+f"(d[57]), "+f"(d[58]), "+f"(d[59]), "+f"(d[60]), "+f"(d[61]), "+f"(d[62]), "+f"(d[63]),
          "+f"(d[64]), "+f"(d[65]), "+f"(d[66]), "+f"(d[67]), "+f"(d[68]), "+f"(d[69]), "+f"(d[70]), "+f"(d[71]),
          "+f"(d[72]), "+f"(d[73]), "+f"(d[74]), "+f"(d[75]), "+f"(d[76]), "+f"(d[77]), "+f"(d[78]), "+f"(d[79]),
          "+f"(d[80]), "+f"(d[81]), "+f"(d[82]), "+f"(d[83]), "+f"(d[84]), "+f"(d[85]), "+f"(d[86]), "+f"(d[87]),
          "+f"(d[88]), "+f"(d[89]), "+f"(d[90]), "+f"(d[91]), "+f"(d[92]), "+f"(d[93]), "+f"(d[94]), "+f"(d[95]),
          "+f"(d[96]), "+f"(d[97]), "+f"(d[98]), "+f"(d[99]), "+f"(d[100]), "+f"(d[101]), "+f"(d[102]), "+f"(d[103]),
          "+f"(d[104]), "+f"(d[105]), "+f"(d[106]), "+f"(d[107]), "+f"(d[108]), "+f"(d[109]), "+f"(d[110]), "+f"(d[111]),
          "+f"(d[112]), "+f"(d[113]), "+f"(d[114]), "+f"(d[115]), "+f"(d[116]), "+f"(d[117]), "+f"(d[118]), "+f"(d[119]),
          "+f"(d[120]), "+f"(d[121]), "+f"(d[122]), "+f"(d[123]), "+f"(d[124]), "+f"(d[125]), "+f"(d[126]), "+f"(d[127])
        : "r"(a0), "r"(a1), "r"(a2), "r"(a3), "l"(db), "r"(scale_d));
}

constexpr float kC1 = 0.25f * 1.4426950408889634f;
constexpr float kC2 = -1.4426950408889634f / 32.0f;
constexpr float kC3 = -4.0f;

template <int V> struct Int { static constexpr int value = V; };
__device__ __forceinline__ uint32_t slot_addr(uint32_t sb, int s) { return sb + SM_SLOT + s * SLOT_BYTES; }
__device__ __forceinline__ uint32_t bar_addr(uint32_t sb, int b) { return sb + SM_BAR + b * 8; }

__device__ __forceinline__ void release_pair(uint32_t bar, uint32_t rank, uint32_t count = 1) {
    mbar_arrive_n(bar, rank, count);
    mbar_arrive_n(bar, rank ^ 1, count);
}

__device__ __forceinline__ float row_bias(uint32_t tile, int row, int half) {
    const uint32_t base = tile + half * 16384 + row * 128;
    const uint32_t sw = ((row & 7) ^ (half << 2)) << 4;
    float s0 = 0.f, s1 = 0.f, s2 = 0.f, s3 = 0.f;
#pragma unroll
    for (int bt = 0; bt < 4; bt++) {
        uint32_t x[4][4];
#pragma unroll
        for (int i = 0; i < 4; i++)
            asm volatile("ld.shared.v4.u32 {%0, %1, %2, %3}, [%4];" : "=r"(x[i][0]), "=r"(x[i][1]), "=r"(x[i][2]), "=r"(x[i][3])
                         : "r"(base + (bt >> 1) * 8192 + ((((bt & 1) * 4 + i) << 4) ^ sw)));
#pragma unroll
        for (int i = 0; i < 4; i++) {
            float a;
            a = __uint_as_float(x[i][0] << 16); s0 = fmaf(a, a, s0);
            a = __uint_as_float(x[i][0] & 0xffff0000u); s1 = fmaf(a, a, s1);
            a = __uint_as_float(x[i][1] << 16); s2 = fmaf(a, a, s2);
            a = __uint_as_float(x[i][1] & 0xffff0000u); s3 = fmaf(a, a, s3);
            a = __uint_as_float(x[i][2] << 16); s0 = fmaf(a, a, s0);
            a = __uint_as_float(x[i][2] & 0xffff0000u); s1 = fmaf(a, a, s1);
            a = __uint_as_float(x[i][3] << 16); s2 = fmaf(a, a, s2);
            a = __uint_as_float(x[i][3] & 0xffff0000u); s3 = fmaf(a, a, s3);
        }
    }
    float s = (s0 + s1) + (s2 + s3);
    s += __shfl_xor_sync(0xffffffffu, s, 1);
    return fmaf(s, kC2, kC3);
}
__device__ __forceinline__ void st_async_f32(uint32_t addr, float v, uint32_t bar, uint32_t cta) {
    asm volatile("{\n.reg .b32 ra, rb;\nmapa.shared::cluster.u32 ra, %0, %3;\nmapa.shared::cluster.u32 rb, %2, %3;\n"
                 "st.async.weak.shared::cluster.mbarrier::complete_tx::bytes.f32 [ra], %1, [rb];\n}"
                 :: "r"(addr), "f"(v), "r"(bar), "r"(cta) : "memory");
}

__device__ __forceinline__ void load_q_frags(uint32_t (&f)[64], float& qb0, float& qb1, uint32_t tile, int wq, int lane) {
    const int row = wq * 16 + (lane & 7) + ((lane >> 3) & 1) * 8;
    const uint32_t base = tile + row * 128;
#pragma unroll
    for (int k = 0; k < 16; k++) {
        const int chunk = 2 * k + (lane >> 4);
        asm volatile("ldmatrix.sync.aligned.m8n8.x4.shared.b16 {%0, %1, %2, %3}, [%4];"
                     : "=r"(f[4 * k]), "=r"(f[4 * k + 1]), "=r"(f[4 * k + 2]), "=r"(f[4 * k + 3])
                     : "r"(base + (k >> 2) * 8192 + (((chunk & 7) ^ (row & 7)) << 4)));
    }
    float s0 = 0.f, s1 = 0.f, s2 = 0.f, s3 = 0.f;
#pragma unroll
    for (int k = 0; k < 32; k++) {
        float a;
        a = __uint_as_float(f[2 * k] << 16); s0 = fmaf(a, a, s0);
        a = __uint_as_float(f[2 * k] & 0xffff0000u); s1 = fmaf(a, a, s1);
        a = __uint_as_float(f[2 * k + 1] << 16); s2 = fmaf(a, a, s2);
        a = __uint_as_float(f[2 * k + 1] & 0xffff0000u); s3 = fmaf(a, a, s3);
    }
    s0 += s1; s2 += s3;
    s0 += __shfl_xor_sync(0xffffffffu, s0, 1); s2 += __shfl_xor_sync(0xffffffffu, s2, 1);
    s0 += __shfl_xor_sync(0xffffffffu, s0, 2); s2 += __shfl_xor_sync(0xffffffffu, s2, 2);
    qb0 = fmaf(s0, kC2, kC3);
    qb1 = fmaf(s2, kC2, kC3);
}
__device__ __forceinline__ void gemm3(float (&d)[64], const uint32_t (&f)[64], uint32_t b01, uint32_t b23) {
    const uint64_t d0 = desc_sw128(b01, 16), d1 = desc_sw128(b23, 16);
    wg_fence();
#pragma unroll
    for (int k = 0; k < 16; k++)
        wgmma_n128_rs(d, f[4 * k], f[4 * k + 1], f[4 * k + 2], f[4 * k + 3],
                      (k < 8 ? d0 : d1) + ((((k >> 2) & 1) * 16384 + (k & 3) * 32) >> 4), k > 0);
    wg_commit();
}
template <int K0>
__device__ __forceinline__ void gemm3_ss(float (&d)[64], uint32_t qs, uint32_t pb) {
    const uint64_t da = desc_sw128(qs + (K0 >> 2) * 8192, 16), db = desc_sw128(pb, 16);
#pragma unroll
    for (int k = 0; k < 8; k++)
        wgmma_n128_ss(d, da + (((k >> 2) * 8192 + (k & 3) * 32) >> 4), db + (((k >> 2) * 16384 + (k & 3) * 32) >> 4), (K0 + k) > 0);
}
template <int K0>
__device__ __forceinline__ void tile_sumsq(float& s0, float& s1, uint32_t tile, int wq, int lane) {
    const int row = wq * 16 + (lane & 7) + ((lane >> 3) & 1) * 8;
    const uint32_t base = tile + row * 128;
    float t0 = 0.f, t1 = 0.f;
#pragma unroll
    for (int kb = 0; kb < 2; kb++) {
        uint32_t x[4][4];
#pragma unroll
        for (int i = 0; i < 4; i++) {
            const int k = K0 + kb * 4 + i, chunk = 2 * k + (lane >> 4);
            asm volatile("ldmatrix.sync.aligned.m8n8.x4.shared.b16 {%0, %1, %2, %3}, [%4];"
                         : "=r"(x[i][0]), "=r"(x[i][1]), "=r"(x[i][2]), "=r"(x[i][3])
                         : "r"(base + (k >> 2) * 8192 + (((chunk & 7) ^ (row & 7)) << 4)));
        }
#pragma unroll
        for (int i = 0; i < 4; i++) {
            float a;
            a = __uint_as_float(x[i][0] << 16); s0 = fmaf(a, a, s0);
            a = __uint_as_float(x[i][0] & 0xffff0000u); t0 = fmaf(a, a, t0);
            a = __uint_as_float(x[i][1] << 16); s1 = fmaf(a, a, s1);
            a = __uint_as_float(x[i][1] & 0xffff0000u); t1 = fmaf(a, a, t1);
            a = __uint_as_float(x[i][2] << 16); s0 = fmaf(a, a, s0);
            a = __uint_as_float(x[i][2] & 0xffff0000u); t0 = fmaf(a, a, t0);
            a = __uint_as_float(x[i][3] << 16); s1 = fmaf(a, a, s1);
            a = __uint_as_float(x[i][3] & 0xffff0000u); t1 = fmaf(a, a, t1);
        }
    }
    s0 += t0;
    s1 += t1;
}
__device__ __forceinline__ void pin_after(float& a, float& b, uint32_t token, uint32_t zero) {
    a = __uint_as_float(__float_as_uint(a) ^ (token & zero));
    b = __uint_as_float(__float_as_uint(b) ^ (token & zero));
}
template <int O>
__device__ __forceinline__ void exp_to_regs(uint32_t (&phi)[64], const float (&a)[64], float qb0, float qb1) {
#pragma unroll
    for (int j = 0; j < 16; j++) {
        phi[O + 2 * j] = pack_bf16(ex2(fmaf(a[4 * j], kC1, qb0)), ex2(fmaf(a[4 * j + 1], kC1, qb0)));
        phi[O + 2 * j + 1] = pack_bf16(ex2(fmaf(a[4 * j + 2], kC1, qb1)), ex2(fmaf(a[4 * j + 3], kC1, qb1)));
    }
}
template <int ID> __device__ __forceinline__ void bar_sync() { asm volatile("bar.sync %0, 256;" :: "n"(ID) : "memory"); }
template <int ID> __device__ __forceinline__ void bar_arrive() { asm volatile("bar.arrive %0, 256;" :: "n"(ID) : "memory"); }

template <int N>
__device__ __forceinline__ void store_out(const float (&o)[N], float inv0, float inv1, __nv_bfloat16* p0) {
#pragma unroll
    for (int t = 0; t < 2; t++) {
#pragma unroll
        for (int i = 0; i < 2; i++) {
            const float inv = i ? inv1 : inv0;
            uint4 v;
            v.x = pack_bf16(o[16 * t + 2 * i] * inv, o[16 * t + 2 * i + 1] * inv);
            v.y = pack_bf16(o[16 * t + 4 + 2 * i] * inv, o[16 * t + 4 + 2 * i + 1] * inv);
            v.z = pack_bf16(o[16 * t + 8 + 2 * i] * inv, o[16 * t + 8 + 2 * i + 1] * inv);
            v.w = pack_bf16(o[16 * t + 12 + 2 * i] * inv, o[16 * t + 12 + 2 * i + 1] * inv);
            *reinterpret_cast<uint4*>(p0 + i * 8 * kDim + t * 32) = v;
        }
    }
}

__global__ void __cluster_dims__(2, 1, 1) __launch_bounds__(384, 1)
performer_kernel(const __grid_constant__ CUtensorMap tm_q, const __grid_constant__ CUtensorMap tm_k,
                 const __grid_constant__ CUtensorMap tm_v, const __grid_constant__ CUtensorMap tm_p,
                 const uint8_t* __restrict__ kptr, const uint8_t* __restrict__ pptr, __nv_bfloat16* __restrict__ out) {
    extern __shared__ __align__(1024) uint8_t smem[];
    const uint32_t sb = (uint32_t)__cvta_generic_to_shared(smem);
    const int tid = threadIdx.x, lane = tid & 31;
    const int warp = __shfl_sync(0xffffffffu, tid >> 5, 0);
    uint32_t rank;
    asm volatile("mov.u32 %0, %%cluster_ctarank;" : "=r"(rank));
    const int cta = blockIdx.x, pair = cta >> 1, h = pair >> 2, sc = pair & 3;

    if (tid == 64) {
        asm volatile("cp.async.bulk.prefetch.L2.global [%0], %1;"
                     :: "l"(kptr + (size_t)(h * kSeq + sc * 512 + rank * 32) * 512), "r"(16384) : "memory");
        asm volatile("cp.async.bulk.prefetch.L2.global [%0], %1;" :: "l"(pptr + cta * 1024), "r"(1024) : "memory");
    }
    if (tid == 32) {
        asm volatile("prefetch.tensormap [%0];" :: "l"(&tm_k) : "memory");
        asm volatile("prefetch.tensormap [%0];" :: "l"(&tm_p) : "memory");
        asm volatile("prefetch.tensormap [%0];" :: "l"(&tm_v) : "memory");
        asm volatile("prefetch.tensormap [%0];" :: "l"(&tm_q) : "memory");
    }
    if (tid == 0) {
        PROF(0);
        mbar_init(bar_addr(sb, B_PROJ), 1);
#pragma unroll
        for (int i = 0; i < 5; i++) { mbar_init(bar_addr(sb, B_FULL + i), 1); mbar_init(bar_addr(sb, B_EMPTY + i), 20); }
#pragma unroll
        for (int i = 0; i < 4; i++) { mbar_init(bar_addr(sb, B_KV + i), 1); mbar_init(bar_addr(sb, B_NORM + i), 1); }
#pragma unroll
        for (int i = 0; i < 2; i++) { mbar_init(bar_addr(sb, B_SFREE + i), 1); mbar_init(bar_addr(sb, B_ACONS + i), 4); }
#pragma unroll
        for (int i = 0; i < 2; i++) mbar_init(bar_addr(sb, B_STG + i), 8);
        mbar_init(bar_addr(sb, B_DUMPED), 1);
        mbar_init(bar_addr(sb, B_PO01), 1);
        mbar_init(bar_addr(sb, B_PO23), 1);
        mbar_init(bar_addr(sb, B_ZERO), 1);
        mbar_init(bar_addr(sb, B_PDEAD), 8);
        mbar_init(bar_addr(sb, B_P0DEAD), 8);
        mbar_init(bar_addr(sb, B_B0DEAD), 4);
        mbar_init(bar_addr(sb, B_KSUM), 1);
        mbar_init(bar_addr(sb, B_GO), 1);
        asm volatile("fence.mbarrier_init.release.cluster;" ::: "memory");
    }
    __syncwarp();
    asm volatile("barrier.cluster.arrive.relaxed.aligned;" ::: "memory");
    asm volatile("barrier.cluster.wait.aligned;" ::: "memory");
    if (tid == 0) {
        const int row0 = h * kSeq + sc * 512;
        const uint64_t pol = policy_evict_first();
        mbar_expect_tx(bar_addr(sb, B_FULL + 0), SLOT_BYTES);
        tma_load_mc(slot_addr(sb, 0) + rank * 16384, &tm_k, bar_addr(sb, B_FULL + 0), row0, rank * 2, pol);
        mbar_expect_tx(bar_addr(sb, B_PROJ), 65536);
        tma_load(sb + SM_P0, &tm_p, bar_addr(sb, B_PROJ), rank * 128, 0);
        tma_load(sb + SM_P0 + 32768, &tm_p, bar_addr(sb, B_PROJ), rank * 128, 2);
        mbar_expect_tx(bar_addr(sb, B_FULL + 1), SLOT_BYTES);
        tma_load_mc(slot_addr(sb, 1) + rank * 16384, &tm_v, bar_addr(sb, B_FULL + 1), row0, rank * 2, pol);
        mbar_expect_tx(bar_addr(sb, B_FULL + 2), SLOT_BYTES);
        tma_load_mc(slot_addr(sb, 2) + rank * 16384, &tm_k, bar_addr(sb, B_FULL + 2), row0 + 64, rank * 2, pol);
    }
    __syncwarp();

    if (warp < 4) {
        reg_dealloc<40>();
        if (warp == 0) {
            if (lane == 0) {
                const int row0 = h * kSeq + sc * 512;
                const uint64_t pol = policy_evict_first();
                auto load_item = [&](int i) {
                    const int s = i % 5;
                    if (i >= 5) mbar_wait(bar_addr(sb, B_EMPTY + s), (i / 5 - 1) & 1);
                    mbar_expect_tx(bar_addr(sb, B_FULL + s), SLOT_BYTES);
                    tma_load_mc(slot_addr(sb, s) + rank * 16384, (i & 1) ? &tm_v : &tm_k, bar_addr(sb, B_FULL + s),
                                row0 + (i >> 1) * 64, rank * 2, pol);
                };
                PROFS(1);
                mbar_wait(bar_addr(sb, B_FULL + 0), 0);
                PROFS(3);
                load_item(3);
                mbar_wait(bar_addr(sb, B_FULL + 1), 0);
                load_item(4);
#pragma unroll 1
                for (int i = 5; i < 16; i++) {
                    load_item(i);
                    if (i == 6) mbar_arrive(bar_addr(sb, B_GO));
                }
                CLKP(0);
                const int qrow = row0 + rank * 256;
                auto load_q = [&](int piece, int slot) {
                    mbar_expect_tx(bar_addr(sb, B_FULL + slot), SLOT_BYTES);
                    tma_load_ef(slot_addr(sb, slot), &tm_q, bar_addr(sb, B_FULL + slot), qrow + piece * 64, 0, pol);
                    tma_load_ef(slot_addr(sb, slot) + 16384, &tm_q, bar_addr(sb, B_FULL + slot), qrow + piece * 64, 2, pol);
                };
                mbar_wait(bar_addr(sb, B_EMPTY + 1), 0);
                load_q(0, S_QA);
                mbar_wait(bar_addr(sb, B_EMPTY + 2), 0);
                mbar_expect_tx(bar_addr(sb, B_PO23), SLOT_BYTES);
                tma_load(slot_addr(sb, S_PO23), &tm_p, bar_addr(sb, B_PO23), (rank ^ 1) * 128, 2);
                CLKP(1);
                mbar_wait(bar_addr(sb, B_EMPTY + 3), 0);
                CLKP(3);
                mbar_expect_tx(bar_addr(sb, B_PO01), SLOT_BYTES);
                tma_load(slot_addr(sb, S_PO01), &tm_p, bar_addr(sb, B_PO01), (rank ^ 1) * 128, 0);
                mbar_wait(bar_addr(sb, B_EMPTY + 4), 0);
                load_q(1, S_QB);
                CLKP(4);
                mbar_wait(bar_addr(sb, B_ACONS + 0), 0);
                load_q(2, S_QA);
                CLKP(7);
                mbar_wait(bar_addr(sb, B_ACONS + 1), 0);
                load_q(3, S_QB);
                CLKP(8);
            }
            __syncwarp();
        } else if (warp < 3) {
            const int w = warp - 1;
            const int row = rank * 32 + w * 16 + (lane >> 1);
            int s = 0, ph = 0;
#pragma unroll 1
            for (int t = 0; t < 8; t++) {
                const uint32_t nbar = bar_addr(sb, B_NORM + (t & 3));
                if (w == 0 && lane == 0) mbar_expect_tx(nbar, 256);
                mbar_wait(bar_addr(sb, B_FULL + s), ph);
                const float b = row_bias(slot_addr(sb, s), row, lane & 1);
                if (!(lane & 1)) {
                    const uint32_t dst = sb + SM_NORM + (t & 3) * 256 + row * 4;
                    st_async_f32(dst, b, nbar, 0);
                    st_async_f32(dst, b, nbar, 1);
                }
                __syncwarp();
                if (lane == 0) release_pair(bar_addr(sb, B_EMPTY + s), rank);
                s += 2;
                if (s >= 5) { s -= 5; ph ^= 1; }
            }
            if (w == 0 && lane == 0) {
                const uint32_t src = slot_addr(sb, S_STG);
                mbar_wait(bar_addr(sb, B_ZERO), 0);
#pragma unroll 1
                for (int r = 0; r < 2; r++) {
                    mbar_wait(bar_addr(sb, B_STG + r), 0);
                    CLKP(17 + r);
                    asm volatile("fence.proxy.async.global;" ::: "memory");
                    if (r == 0)
                        asm volatile("cp.reduce.async.bulk.global.shared::cta.bulk_group.add.f32 [%0], [%1], %2;"
                                     :: "l"(g_ksum + h * 256 + rank * 128), "r"(sb + SM_KS), "r"(512) : "memory");
#pragma unroll 1
                    for (int b = 0; b < 8; b++) {
                        const int g2 = b >> 2, u = (b >> 1) & 1, hf = b & 1;
                        uint8_t* dst = reinterpret_cast<uint8_t*>(g_kvacc + h * 8192) + (2 * r + u) * 32768 + (rank * 128 + g2 * 64 + hf * 32) * 128;
                        asm volatile("cp.reduce.async.bulk.global.shared::cta.bulk_group.add.noftz.bf16 [%0], [%1], %2;"
                                     :: "l"(dst), "r"(src + b * 4096), "r"(4096) : "memory");
                        asm volatile("cp.async.bulk.commit_group;" ::: "memory");
                        asm volatile("cp.async.bulk.wait_group.read 0;" ::: "memory");
                    }
                    mbar_arrive(bar_addr(sb, B_SFREE + r));
                    CLKP(9 + r);
                    asm volatile("cp.async.bulk.wait_group 0;" ::: "memory");
                    asm volatile("fence.proxy.async.global;" ::: "memory");
                    red_add_u32(&g_flag_dump[h * 64 + r * 32], 1);
                    if (r == 0) mbar_arrive(bar_addr(sb, B_DUMPED));
                    CLKP(12 + 2 * r);
                }
            }
            __syncwarp();
        } else {
            unsigned target = 0;
            if (lane == 0) target = ld_relaxed_gpu(&g_flag_dump[h * 64 + 32]) + 8;
            mbar_wait(bar_addr(sb, B_GO), 0);
            uint4* z = g_kvacc + h * 8192 + (cta & 7) * 1024;
#pragma unroll 4
            for (int i = 0; i < 32; i++) z[i * 32 + lane] = make_uint4(0, 0, 0, 0);
            g_ksum[h * 256 + (cta & 7) * 32 + lane] = 0.f;
            __syncwarp();
            if (lane == 0) {
                fence_gpu();
                red_add_u32(&g_flag_zero[h * 32], 1);
                spin_flag(&g_flag_zero[h * 32], target);
                asm volatile("fence.proxy.async.global;" ::: "memory");
                mbar_arrive(bar_addr(sb, B_ZERO));
                mbar_wait(bar_addr(sb, B_DUMPED), 0);
                spin_flag(&g_flag_dump[h * 64], target);
                asm volatile("fence.proxy.async.global;" ::: "memory");
                CLKP(15);
            }
            __syncwarp();
            float kv8[8];
#pragma unroll
            for (int i = 0; i < 8; i++) kv8[i] = __ldcg(g_ksum + h * 256 + i * 32 + lane);
            const uint8_t* kvsrc = reinterpret_cast<const uint8_t*>(g_kvacc + h * 8192);
            if (lane == 0) {
                mbar_wait(bar_addr(sb, B_SFREE + 1), 0);
                mbar_expect_tx(bar_addr(sb, B_KV + 0), SLOT_BYTES);
                bulk_load(slot_addr(sb, S_STG), kvsrc, SLOT_BYTES, bar_addr(sb, B_KV + 0));
                mbar_wait(bar_addr(sb, B_P0DEAD), 0);
                mbar_expect_tx(bar_addr(sb, B_KV + 1), SLOT_BYTES);
                bulk_load(sb + SM_P0, kvsrc + 32768, SLOT_BYTES, bar_addr(sb, B_KV + 1));
            }
            __syncwarp();
            if (lane == 0) CLKP(5);
            mbar_wait(bar_addr(sb, B_B0DEAD), 0);
            if (lane == 0) CLKP(6);
#pragma unroll
            for (int i = 0; i < 8; i++) {
                const int m = i * 32 + lane;
                asm volatile("st.shared.v4.u32 [%0], {%1, %1, %1, %1};" :: "r"(slot_addr(sb, S_QA) + m * 128 + ((m & 7) << 4)), "r"(pack_bf16(kv8[i], kv8[i])) : "memory");
            }
            if (lane == 0) CLKP(11);
            asm volatile("fence.proxy.async.shared::cta;" ::: "memory");
            __syncwarp();
            if (lane == 0) {
                mbar_arrive(bar_addr(sb, B_KSUM));
                CLKP(16);
                spin_flag(&g_flag_dump[h * 64 + 32], target);
                asm volatile("fence.proxy.async.global;" ::: "memory");
                mbar_expect_tx(bar_addr(sb, B_KV + 2), SLOT_BYTES);
                bulk_load(sb + SM_P0 + 32768, kvsrc + 65536, SLOT_BYTES, bar_addr(sb, B_KV + 2));
                mbar_wait(bar_addr(sb, B_PDEAD), 0);
                mbar_expect_tx(bar_addr(sb, B_KV + 3), SLOT_BYTES);
                bulk_load(slot_addr(sb, S_PO01), kvsrc + 98304, SLOT_BYTES, bar_addr(sb, B_KV + 3));
            }
            __syncwarp();
        }
        asm volatile("barrier.cluster.arrive.relaxed.aligned;" ::: "memory");
        asm volatile("barrier.cluster.wait.aligned;" ::: "memory");
    } else {
        reg_alloc<232>();
        const int w = (warp - 4) >> 2, wq = warp & 3, g = lane >> 2, c = lane & 3;
        float ks0 = 0.f, ks1 = 0.f, qb0, qb1;
        uint32_t f[64], pk[64];
        auto stage = [&](auto round) {
            constexpr int R = decltype(round)::value;
            const uint32_t stg = slot_addr(sb, S_STG) + w * 16384 + (wq * 16 + g) * 128;
            const bool odd = g & 1;
            const uint32_t o0 = (((odd ? 4 : 0) + c) ^ g) << 4, o1 = (((odd ? 0 : 4) + c) ^ g) << 4;
#pragma unroll
            for (int u = 0; u < 2; u++)
#pragma unroll
                for (int i = 0; i < 2; i++) {
                    const uint32_t* e = pk + 16 * (2 * R + u) + 4 * i;
                    asm volatile("st.shared.v4.u32 [%0], {%1, %2, %3, %4};" :: "r"(stg + u * 8192 + i * 1024 + o0),
                                 "r"(odd ? e[8] : e[0]), "r"(odd ? e[9] : e[1]), "r"(odd ? e[10] : e[2]), "r"(odd ? e[11] : e[3]) : "memory");
                    asm volatile("st.shared.v4.u32 [%0], {%1, %2, %3, %4};" :: "r"(stg + u * 8192 + i * 1024 + o1),
                                 "r"(odd ? e[0] : e[8]), "r"(odd ? e[1] : e[9]), "r"(odd ? e[2] : e[10]), "r"(odd ? e[3] : e[11]) : "memory");
                }
            asm volatile("fence.proxy.async.shared::cta;" ::: "memory");
            __syncwarp();
            if (lane == 0) mbar_arrive(bar_addr(sb, B_STG + R));
        };
        {
            float acc[128];
            uint32_t p[16];
            const uint64_t dp = desc_sw128(sb + SM_P0 + w * 8192, 16);
            mbar_wait(bar_addr(sb, B_PROJ), 0);
            PROFA(0); CLKS(28);
            uint32_t pf[4 * kG1Rs];
            {
                const int row = w * 64 + wq * 16 + (lane & 7) + ((lane >> 3) & 1) * 8;
#pragma unroll
                for (int k = 0; k < kG1Rs; k++) {
                    const int chunk = 2 * k + (lane >> 4);
                    asm volatile("ldmatrix.sync.aligned.m8n8.x4.shared.b16 {%0, %1, %2, %3}, [%4];"
                                 : "=r"(pf[4 * k]), "=r"(pf[4 * k + 1]), "=r"(pf[4 * k + 2]), "=r"(pf[4 * k + 3])
                                 : "r"(sb + SM_P0 + (k >> 2) * 16384 + row * 128 + (((chunk & 7) ^ (row & 7)) << 4)));
                }
            }
            int ks = 0, kph = 0;
#pragma unroll 1
            for (int t = 0; t < 8; t++) {
                float s[32];
                const int vs = ks == 0 ? 4 : ks - 1, vph = ks == 0 ? kph ^ 1 : kph;
                CLK(0);
                if (w == 1) bar_sync<2>(); else if (t > 0) bar_sync<3>();
                CLK(1);
                if (t > 0) {
                    mbar_wait(bar_addr(sb, B_FULL + vs), vph);
                    const uint64_t dv = desc_sw128(slot_addr(sb, vs), 8192);
                    wg_fence();
#pragma unroll
                    for (int k = 0; k < 4; k++)
                        wgmma_n256_rs_tb(acc, p[4 * k], p[4 * k + 1], p[4 * k + 2], p[4 * k + 3], dv + ((k * 2048) >> 4), (t - 1 + k) > 0);
                    wg_commit();
                }
                CLK(2);
                mbar_wait(bar_addr(sb, B_FULL + ks), kph);
                const uint64_t dk = desc_sw128(slot_addr(sb, ks), 16);
                wg_fence();
#pragma unroll
                for (int k = 0; k < 16; k++) {
                    if (k < kG1Rs)
                        wgmma_n64_rs(s, pf[4 * k], pf[4 * k + 1], pf[4 * k + 2], pf[4 * k + 3], dk + (((k >> 2) * 8192 + (k & 3) * 32) >> 4), k > 0);
                    else
                        wgmma_n64_ss(s, dp + (((k >> 2) * 16384 + (k & 3) * 32) >> 4), dk + (((k >> 2) * 8192 + (k & 3) * 32) >> 4), k > 0);
                }
                wg_commit();
                if (w == 0) bar_arrive<2>(); else bar_arrive<3>();
                CLK(3);
                if (t > 0) {
                    wg_wait<1>();
                    if (lane == 0) release_pair(bar_addr(sb, B_EMPTY + vs), rank, wq == 0 ? 2 : 1);
                }
                CLK(4);
                wg_wait<0>();
                CLK(5);
                CLKALL(t);
                if (lane == 0) release_pair(bar_addr(sb, B_EMPTY + ks), rank);
                mbar_wait(bar_addr(sb, B_NORM + (t & 3)), (t >> 2) & 1);
                CLK(6);
                const uint32_t nb = sb + SM_NORM + (t & 3) * 256 + c * 8;
                float bias[16];
#pragma unroll
                for (int j = 0; j < 8; j++)
                    asm volatile("ld.shared.v2.f32 {%0, %1}, [%2];" : "=f"(bias[2 * j]), "=f"(bias[2 * j + 1]) : "r"(nb + j * 32) : "memory");
#pragma unroll
                for (int j = 0; j < 8; j++) {
                    const float bx = bias[2 * j], by = bias[2 * j + 1];
                    const float p00 = ex2(fmaf(s[4 * j], kC1, bx)), p01 = ex2(fmaf(s[4 * j + 1], kC1, by));
                    const float p10 = ex2(fmaf(s[4 * j + 2], kC1, bx)), p11 = ex2(fmaf(s[4 * j + 3], kC1, by));
                    ks0 += p00 + p01;
                    ks1 += p10 + p11;
                    p[2 * j] = pack_bf16(p00, p01);
                    p[2 * j + 1] = pack_bf16(p10, p11);
                }
                CLK(7);
                ks += 2;
                if (ks >= 5) { ks -= 5; kph ^= 1; }
            }
            if (w == 1) bar_sync<2>(); else bar_sync<3>();
            mbar_wait(bar_addr(sb, B_FULL + 0), 1);
            {
                const uint64_t dv = desc_sw128(slot_addr(sb, 0), 8192);
                wg_fence();
#pragma unroll
                for (int k = 0; k < 4; k++)
                    wgmma_n256_rs_tb(acc, p[4 * k], p[4 * k + 1], p[4 * k + 2], p[4 * k + 3], dv + ((k * 2048) >> 4), 1);
                wg_commit();
            }
            if (w == 0) bar_arrive<2>();
            wg_wait<0>();
            PROFA(6); CLKS(11);
            ks0 += __shfl_xor_sync(0xffffffffu, ks0, 1); ks0 += __shfl_xor_sync(0xffffffffu, ks0, 2);
            ks1 += __shfl_xor_sync(0xffffffffu, ks1, 1); ks1 += __shfl_xor_sync(0xffffffffu, ks1, 2);
            if (c == 0) {
                asm volatile("st.shared.f32 [%0], %1;" :: "r"(sb + SM_KS + (w * 64 + wq * 16 + g) * 4), "f"(ks0) : "memory");
                asm volatile("st.shared.f32 [%0], %1;" :: "r"(sb + SM_KS + (w * 64 + wq * 16 + g + 8) * 4), "f"(ks1) : "memory");
            }
#pragma unroll
            for (int t = 0; t < 8; t++)
#pragma unroll
                for (int i = 0; i < 2; i++)
#pragma unroll
                    for (int jj = 0; jj < 4; jj++)
                        pk[8 * t + 4 * i + jj] = pack_bf16(acc[16 * t + 4 * jj + 2 * i], acc[16 * t + 4 * jj + 2 * i + 1]);
            auto load_a = [&]() {
                mbar_wait(bar_addr(sb, B_FULL + (w == 0 ? S_QA : S_QB)), 1);
                PROFW(8); CLKS(13);
                load_q_frags(f, qb0, qb1, slot_addr(sb, w == 0 ? S_QA : S_QB), wq, lane);
                asm volatile("fence.proxy.async.shared::cta;" ::: "memory");
                __syncwarp();
                if (lane == 0) mbar_arrive(bar_addr(sb, B_ACONS + w));
            };
            bar_sync<3>();
            stage(Int<0>{});
            PROFW(7); CLKS(12);
            load_a();
            PROFW(9); CLKS(14);
        }

        uint32_t phi[64], phib[64];
        const uint32_t qsb = slot_addr(sb, w == 0 ? S_QA : S_QB);
        {
            const uint32_t p0 = sb + SM_P0, po01 = slot_addr(sb, S_PO01), po23 = slot_addr(sb, S_PO23);
            float a[64];
            gemm3(a, f, p0, p0 + 32768);
            PROFW(10); CLKS(15);
            wg_wait<0>();
            PROFW(11); CLKS(16);
            exp_to_regs<0>(phi, a, qb0, qb1);
            PROFW(12); CLKS(17);
            if (w == 1) {
                mbar_wait(bar_addr(sb, B_SFREE + 0), 0);
                stage(Int<1>{});
            }
            mbar_wait(bar_addr(sb, B_PO01), 0);
            mbar_wait(bar_addr(sb, B_PO23), 0);
            PROFW(13); CLKS(18);
            gemm3(a, f, po01, po23);
            PROFW(14); CLKS(19);
            if (w == 0) {
                mbar_wait(bar_addr(sb, B_SFREE + 0), 0);
                stage(Int<1>{});
            }
            wg_wait<0>();
            PROFW(16); CLKS(20);
            exp_to_regs<32>(phi, a, qb0, qb1);
            mbar_wait(bar_addr(sb, B_FULL + (w == 0 ? S_QA : S_QB)), 0);
            PROFW(17); CLKS(21);
            float s0 = 0.f, s1 = 0.f;
            wg_fence();
            gemm3_ss<0>(a, qsb, p0);
            tile_sumsq<0>(s0, s1, qsb, wq, lane);
            gemm3_ss<8>(a, qsb, p0 + 32768);
            wg_commit();
            tile_sumsq<8>(s0, s1, qsb, wq, lane);
            s0 += __shfl_xor_sync(0xffffffffu, s0, 1); s1 += __shfl_xor_sync(0xffffffffu, s1, 1);
            s0 += __shfl_xor_sync(0xffffffffu, s0, 2); s1 += __shfl_xor_sync(0xffffffffu, s1, 2);
            qb0 = fmaf(s0, kC2, kC3);
            qb1 = fmaf(s1, kC2, kC3);
            PROFW(18); CLKS(22);
            wg_wait<0>();
            PROFW(19); CLKS(23);
            pin_after(qb0, qb1, mbar_arrive_lane0(bar_addr(sb, B_P0DEAD), lane), rank >> 8);
            exp_to_regs<0>(phib, a, qb0, qb1);
            wg_fence();
            gemm3_ss<0>(a, qsb, po01);
            gemm3_ss<8>(a, qsb, po23);
            wg_commit();
            wg_wait<0>();
            PROFW(21); CLKS(24);
            if (w == 0 && lane == 0) mbar_arrive(bar_addr(sb, B_B0DEAD));
            pin_after(qb0, qb1, mbar_arrive_lane0(bar_addr(sb, B_PDEAD), lane), rank >> 8);
            exp_to_regs<32>(phib, a, qb0, qb1);
            PROFW(22); CLKS(25);
        }
        asm volatile("barrier.cluster.arrive.relaxed.aligned;" ::: "memory");
        {
            const uint32_t kvb[4] = {slot_addr(sb, S_STG), sb + SM_P0, sb + SM_P0 + 32768, slot_addr(sb, S_PO01)};
            const uint32_t mo = rank * 128 * 128, mx = (rank ^ 1) * 128 * 128;
            const int orow = h * kSeq + sc * 512 + rank * 256 + w * 64 + wq * 16 + g;
            __nv_bfloat16* pA = out + (size_t)orow * kDim + c * 8;
            __nv_bfloat16* pB = pA + 128 * kDim;
            float iA0, iA1, iB0, iB1;
            auto take_turn = [&](bool first) { if (w == 1) bar_sync<2>(); else if (!first) bar_sync<3>(); };
            auto give_turn = [&](bool last) { if (w == 0) bar_arrive<2>(); else if (!last) bar_arrive<3>(); };
            {
                float e[36];
                const uint32_t lbo = slot_addr(sb, S_QA) - slot_addr(sb, S_STG);
                auto tile0 = [&](const uint32_t (&ph)[64], bool first) {
                    const uint64_t d0 = desc_sw128(kvb[0] + mo, lbo), d1 = desc_sw128(kvb[0] + mx, lbo);
                    take_turn(first);
                    wg_fence();
#pragma unroll
                    for (int k = 0; k < 16; k++)
                        wgmma_n72_rs_tb(e, ph[4 * k], ph[4 * k + 1], ph[4 * k + 2], ph[4 * k + 3], (k < 8 ? d0 : d1) + (((k & 7) * 2048) >> 4), k > 0);
                    wg_commit();
                    give_turn(false);
                    wg_wait<0>();
                };
                mbar_wait(bar_addr(sb, B_KV + 0), 0);
                mbar_wait(bar_addr(sb, B_KSUM), 0);
                PROFA(23); CLKS(26);
                tile0(phi, true);
                iA0 = __fdividef(1.f, e[32] + 1e-6f);
                iA1 = __fdividef(1.f, e[34] + 1e-6f);
                store_out(e, iA0, iA1, pA);
                CLKG4(0);
                tile0(phib, false);
                iB0 = __fdividef(1.f, e[32] + 1e-6f);
                iB1 = __fdividef(1.f, e[34] + 1e-6f);
                store_out(e, iB0, iB1, pB);
                CLKG4(1);
            }
#pragma unroll
            for (int i = 2; i < 8; i++) {
                const int b = i >> 1;
                float o[32];
                const uint64_t d0 = desc_sw128(kvb[b] + mo, 16), d1 = desc_sw128(kvb[b] + mx, 16);
                if (!(i & 1)) mbar_wait(bar_addr(sb, B_KV + b), 0);
                take_turn(false);
                wg_fence();
#pragma unroll
                for (int k = 0; k < 16; k++) {
                    const uint32_t (&ph)[64] = (i & 1) ? phib : phi;
                    wgmma_n64_rs_tb(o, ph[4 * k], ph[4 * k + 1], ph[4 * k + 2], ph[4 * k + 3], (k < 8 ? d0 : d1) + (((k & 7) * 2048) >> 4), k > 0);
                }
                wg_commit();
                give_turn(i == 7);
                wg_wait<0>();
                if (i & 1) store_out(o, iB0, iB1, pB + b * 64); else store_out(o, iA0, iA1, pA + b * 64);
                CLKG4(i);
            }
        }
        PROFA(24);
        CLKS(27);
        asm volatile("barrier.cluster.wait.aligned;" ::: "memory");
    }
}

typedef CUresult (*EncodeTiledFn)(CUtensorMap*, CUtensorMapDataType, cuuint32_t, void*, const cuuint64_t*, const cuuint64_t*,
                                  const cuuint32_t*, const cuuint32_t*, CUtensorMapInterleave, CUtensorMapSwizzle,
                                  CUtensorMapL2promotion, CUtensorMapFloatOOBfill);

bool make_map(EncodeTiledFn enc, CUtensorMap* m, const void* base, uint64_t rows, uint32_t box_rows) {
    cuuint64_t dims[3] = {64, rows, 4};
    cuuint64_t strides[2] = {512, 128};
    cuuint32_t box[3] = {64, box_rows, 2};
    cuuint32_t es[3] = {1, 1, 1};
    return enc(m, CU_TENSOR_MAP_DATA_TYPE_BFLOAT16, 3, const_cast<void*>(base), dims, strides, box, es,
               CU_TENSOR_MAP_INTERLEAVE_NONE, CU_TENSOR_MAP_SWIZZLE_128B, CU_TENSOR_MAP_L2_PROMOTION_L2_256B,
               CU_TENSOR_MAP_FLOAT_OOB_FILL_NONE) == CUDA_SUCCESS;
}

}

extern "C" void kernel_launch(void* const* d_in, const int* in_sizes, int n_in, void* d_out, int out_size) {
    (void)in_sizes; (void)n_in; (void)out_size;
    static EncodeTiledFn enc = nullptr;
    if (!enc) {
        void* fn = nullptr;
        cudaDriverEntryPointQueryResult qr;
        if (cudaGetDriverEntryPoint("cuTensorMapEncodeTiled", &fn, cudaEnableDefault, &qr) != cudaSuccess || !fn) return;
        enc = (EncodeTiledFn)fn;
        cudaFuncSetAttribute(performer_kernel, cudaFuncAttributeMaxDynamicSharedMemorySize, SM_TOTAL);
    }
    CUtensorMap tq, tk, tv, tp;
    if (!make_map(enc, &tq, d_in[0], kHeads * kSeq, 64) || !make_map(enc, &tk, d_in[1], kHeads * kSeq, 64) ||
        !make_map(enc, &tv, d_in[2], kHeads * kSeq, 64) || !make_map(enc, &tp, d_in[3], 256, 128)) return;
    performer_kernel<<<128, 384, SM_TOTAL, cudaStreamPerThread>>>(tq, tk, tv, tp, (const uint8_t*)d_in[1], (const uint8_t*)d_in[3],
                                                                    (__nv_bfloat16*)d_out);
}
```

```cpp
#include <cuda_runtime.h>
#include <cuda_bf16.h>
#include <cuda.h>
#include <stdint.h>

namespace {

constexpr int kHeads = 16;
constexpr int kSeq = 2048;
constexpr int kDim = 256;

constexpr uint32_t SM_P0 = 0;
constexpr uint32_t SM_SLOT = 65536;
constexpr uint32_t SLOT_BYTES = 32768;
constexpr uint32_t SM_BAR = SM_SLOT + 5 * SLOT_BYTES;
constexpr uint32_t SM_NORM = SM_BAR + 512;
constexpr uint32_t SM_KS = SM_NORM + 1024;
constexpr uint32_t SM_TOTAL = SM_KS + 512;

constexpr int S_STG = 0, S_QA = 1, S_PO23 = 2, S_PO01 = 3, S_QB = 4;

constexpr int B_PROJ = 0;
constexpr int B_FULL = 1;
constexpr int B_EMPTY = 6;
constexpr int B_NORM = 11;
constexpr int B_KV = 15;
constexpr int B_STG = 19;
constexpr int B_GO = 21;
constexpr int B_ACONS = 22;
constexpr int B_SFREE = 24;
constexpr int B_PO01 = 26;
constexpr int B_PO23 = 27;
constexpr int B_ZERO = 28;
constexpr int B_PDEAD = 29;
constexpr int B_B0DEAD = 30;
constexpr int B_KSUM = 31;
constexpr int B_DUMPED = 32;
constexpr int B_P0DEAD = 33;
constexpr int B_QARR = 34;

constexpr int kG1Rs = 7;
constexpr int kSpinLimit = 1 << 21;

__device__ uint4 g_kvacc[kHeads * 8192];
__device__ float g_ksum[kHeads * 256];
__device__ unsigned g_flag_zero[kHeads * 32];
__device__ unsigned g_flag_dump[kHeads * 64];
#define PROF(i) do {} while (0)
#define PROFW(i) do {} while (0)
#define PROFA(i) do {} while (0)
#define PROFS(i) do {} while (0)
#define CLK(i) do {} while (0)
#define CLKS(i) do {} while (0)
#define CLKP(i) do {} while (0)
#define CLKALL(i) do {} while (0)
#define CLKG4(i) do {} while (0)

__device__ __forceinline__ void mbar_init(uint32_t bar, uint32_t cnt) {
    asm volatile("mbarrier.init.shared::cta.b64 [%0], %1;" :: "r"(bar), "r"(cnt) : "memory");
}
__device__ __forceinline__ void mbar_expect_tx(uint32_t bar, uint32_t bytes) {
    asm volatile("mbarrier.arrive.expect_tx.shared::cta.b64 _, [%0], %1;" :: "r"(bar), "r"(bytes) : "memory");
}
__device__ __forceinline__ void mbar_arrive(uint32_t bar) {
    asm volatile("mbarrier.arrive.shared::cta.b64 _, [%0];" :: "r"(bar) : "memory");
}
__device__ __forceinline__ uint32_t mbar_arrive_lane0(uint32_t bar, int lane) {
    uint32_t lo;
    asm volatile("{\n.reg .pred p;\n.reg .b64 st;\n.reg .b32 hi;\nmov.b64 st, 0;\nsetp.eq.s32 p, %2, 0;\n"
                 "@p mbarrier.arrive.shared::cta.b64 st, [%1];\nmov.b64 {%0, hi}, st;\n}" : "=r"(lo) : "r"(bar), "r"(lane) : "memory");
    return lo;
}
__device__ __forceinline__ void mbar_arrive_n(uint32_t bar, uint32_t cta, uint32_t count) {
    asm volatile("{\n.reg .b32 ra;\nmapa.shared::cluster.u32 ra, %0, %1;\n"
                 "mbarrier.arrive.shared::cluster.b64 _, [ra], %2;\n}" :: "r"(bar), "r"(cta), "r"(count) : "memory");
}
__device__ __forceinline__ void mbar_wait(uint32_t bar, uint32_t parity) {
    uint32_t ok;
    int it = 0;
    do {
        asm volatile("{\n.reg .pred p;\nmbarrier.try_wait.parity.shared::cta.b64 p, [%1], %2;\nselp.u32 %0, 1, 0, p;\n}"
                     : "=r"(ok) : "r"(bar), "r"(parity) : "memory");
    } while (!ok && ++it < kSpinLimit);
}
__device__ __forceinline__ void tma_load(uint32_t dst, const CUtensorMap* tm, uint32_t bar, int row, int blk) {
    asm volatile("cp.async.bulk.tensor.3d.shared::cluster.global.mbarrier::complete_tx::bytes [%0], [%1, {%3, %4, %5}], [%2];"
                 :: "r"(dst), "l"(tm), "r"(bar), "r"(0), "r"(row), "r"(blk) : "memory");
}
__device__ __forceinline__ uint64_t policy_evict_first() {
    uint64_t p;
    asm volatile("createpolicy.fractional.L2::evict_first.b64 %0, 1.0;" : "=l"(p));
    return p;
}
__device__ __forceinline__ void tma_load_ef(uint32_t dst, const CUtensorMap* tm, uint32_t bar, int row, int blk, uint64_t pol) {
    asm volatile("cp.async.bulk.tensor.3d.shared::cluster.global.mbarrier::complete_tx::bytes.L2::cache_hint [%0], [%1, {%3, %4, %5}], [%2], %6;"
                 :: "r"(dst), "l"(tm), "r"(bar), "r"(0), "r"(row), "r"(blk), "l"(pol) : "memory");
}
__device__ __forceinline__ void tma_load_mc(uint32_t dst, const CUtensorMap* tm, uint32_t bar, int row, int blk, uint64_t pol) {
    asm volatile("cp.async.bulk.tensor.3d.shared::cluster.global.mbarrier::complete_tx::bytes.multicast::cluster.L2::cache_hint [%0], [%1, {%3, %4, %5}], [%2], %6, %7;"
                 :: "r"(dst), "l"(tm), "r"(bar), "r"(0), "r"(row), "r"(blk), "h"((uint16_t)3), "l"(pol) : "memory");
}
__device__ __forceinline__ void bulk_load(uint32_t dst, const void* src, uint32_t bytes, uint32_t bar) {
    asm volatile("cp.async.bulk.shared::cluster.global.mbarrier::complete_tx::bytes [%0], [%1], %2, [%3];"
                 :: "r"(dst), "l"(src), "r"(bytes), "r"(bar) : "memory");
}
__device__ __forceinline__ void wg_fence() { asm volatile("wgmma.fence.sync.aligned;" ::: "memory"); }
__device__ __forceinline__ void wg_commit() { asm volatile("wgmma.commit_group.sync.aligned;" ::: "memory"); }
template <int N> __device__ __forceinline__ void wg_wait() { asm volatile("wgmma.wait_group.sync.aligned %0;" :: "n"(N) : "memory"); }

__device__ __forceinline__ uint64_t desc_sw128(uint32_t addr, uint32_t lbo) {
    asm volatile("" : "+r"(addr));
    return (uint64_t)((addr & 0x3FFFF) >> 4) | ((uint64_t)(lbo >> 4) << 16) | ((uint64_t)(1024 >> 4) << 32) | (1ull << 62);
}
__device__ __forceinline__ uint32_t pack_bf16(float lo, float hi) {
    uint32_t r;
    asm("cvt.rn.bf16x2.f32 %0, %1, %2;" : "=r"(r) : "f"(hi), "f"(lo));
    return r;
}
__device__ __forceinline__ float ex2(float x) {
    float y;
    asm("ex2.approx.ftz.f32 %0, %1;" : "=f"(y) : "f"(x));
    return y;
}
__device__ __forceinline__ unsigned ld_relaxed_gpu(const unsigned* p) {
    unsigned v;
    asm volatile("ld.relaxed.gpu.global.u32 %0, [%1];" : "=r"(v) : "l"(p) : "memory");
    return v;
}
__device__ __forceinline__ void fence_gpu() { asm volatile("fence.acq_rel.gpu;" ::: "memory"); }
__device__ __forceinline__ void red_add_u32(unsigned* p, unsigned v) {
    asm volatile("red.relaxed.gpu.global.add.u32 [%0], %1;" :: "l"(p), "r"(v) : "memory");
}
__device__ __forceinline__ unsigned ld_acquire_gpu(const unsigned* p) {
    unsigned v;
    asm volatile("ld.acquire.gpu.global.u32 %0, [%1];" : "=r"(v) : "l"(p) : "memory");
    return v;
}
__device__ __forceinline__ void spin_flag(const unsigned* p, unsigned target) {
    int it = 0;
    while ((int)(ld_acquire_gpu(p) - target) < 0 && ++it < kSpinLimit) {}
}
template <int R> __device__ __forceinline__ void reg_alloc() { asm volatile("setmaxnreg.inc.sync.aligned.u32 %0;" :: "n"(R)); }
template <int R> __device__ __forceinline__ void reg_dealloc() { asm volatile("setmaxnreg.dec.sync.aligned.u32 %0;" :: "n"(R)); }

template <int N>
__device__ __forceinline__ void wgmma_n64_ss(float (&d)[N], uint64_t da, uint64_t db, int scale_d) {
    asm volatile("{\n.reg .pred p;\nsetp.ne.b32 p, %34, 0;\n"
        "wgmma.mma_async.sync.aligned.m64n64k16.f32.bf16.bf16 "
        "{%0, %1, %2, %3, %4, %5, %6, %7, %8, %9, %10, %11, %12, %13, %14, %15, "
        "%16, %17, %18, %19, %20, %21, %22, %23, %24, %25, %26, %27, %28, %29, %30, %31}, "
        "%32, %33, p, 1, 1, 0, 0;\n}\n"
        : "+f"(d[0]), "+f"(d[1]), "+f"(d[2]), "+f"(d[3]), "+f"(d[4]), "+f"(d[5]), "+f"(d[6]), "+f"(d[7]),
          "+f"(d[8]), "+f"(d[9]), "+f"(d[10]), "+f"(d[11]), "+f"(d[12]), "+f"(d[13]), "+f"(d[14]), "+f"(d[15]),
          "+f"(d[16]), "+f"(d[17]), "+f"(d[18]), "+f"(d[19]), "+f"(d[20]), "+f"(d[21]), "+f"(d[22]), "+f"(d[23]),
          "+f"(d[24]), "+f"(d[25]), "+f"(d[26]), "+f"(d[27]), "+f"(d[28]), "+f"(d[29]), "+f"(d[30]), "+f"(d[31])
        : "l"(da), "l"(db), "r"(scale_d));
}
template <int N>
__device__ __forceinline__ void wgmma_n64_rs(float (&d)[N], uint32_t a0, uint32_t a1, uint32_t a2, uint32_t a3, uint64_t db, int scale_d) {
    asm volatile("{\n.reg .pred p;\nsetp.ne.b32 p, %37, 0;\n"
        "wgmma.mma_async.sync.aligned.m64n64k16.f32.bf16.bf16 "
        "{%0, %1, %2, %3, %4, %5, %6, %7, %8, %9, %10, %11, %12, %13, %14, %15, "
        "%16, %17, %18, %19, %20, %21, %22, %23, %24, %25, %26, %27, %28, %29, %30, %31}, "
        "{%32, %33, %34, %35}, %36, p, 1, 1, 0;\n}\n"
        : "+f"(d[0]), "+f"(d[1]), "+f"(d[2]), "+f"(d[3]), "+f"(d[4]), "+f"(d[5]), "+f"(d[6]), "+f"(d[7]),
          "+f"(d[8]), "+f"(d[9]), "+f"(d[10]), "+f"(d[11]), "+f"(d[12]), "+f"(d[13]), "+f"(d[14]), "+f"(d[15]),
          "+f"(d[16]), "+f"(d[17]), "+f"(d[18]), "+f"(d[19]), "+f"(d[20]), "+f"(d[21]), "+f"(d[22]), "+f"(d[23]),
          "+f"(d[24]), "+f"(d[25]), "+f"(d[26]), "+f"(d[27]), "+f"(d[28]), "+f"(d[29]), "+f"(d[30]), "+f"(d[31])
        : "r"(a0), "r"(a1), "r"(a2), "r"(a3), "l"(db), "r"(scale_d));
}
template <int N>
__device__ __forceinline__ void wgmma_n64_rs_tb(float (&d)[N], uint32_t a0, uint32_t a1, uint32_t a2, uint32_t a3, uint64_t db, int scale_d) {
    asm volatile("{\n.reg .pred p;\nsetp.ne.b32 p, %37, 0;\n"
        "wgmma.mma_async.sync.aligned.m64n64k16.f32.bf16.bf16 "
        "{%0, %1, %2, %3, %4, %5, %6, %7, %8, %9, %10, %11, %12, %13, %14, %15, "
        "%16, %17, %18, %19, %20, %21, %22, %23, %24, %25, %26, %27, %28, %29, %30, %31}, "
        "{%32, %33, %34, %35}, %36, p, 1, 1, 1;\n}\n"
        : "+f"(d[0]), "+f"(d[1]), "+f"(d[2]), "+f"(d[3]), "+f"(d[4]), "+f"(d[5]), "+f"(d[6]), "+f"(d[7]),
          "+f"(d[8]), "+f"(d[9]), "+f"(d[10]), "+f"(d[11]), "+f"(d[12]), "+f"(d[13]), "+f"(d[14]), "+f"(d[15]),
          "+f"(d[16]), "+f"(d[17]), "+f"(d[18]), "+f"(d[19]), "+f"(d[20]), "+f"(d[21]), "+f"(d[22]), "+f"(d[23]),
          "+f"(d[24]), "+f"(d[25]), "+f"(d[26]), "+f"(d[27]), "+f"(d[28]), "+f"(d[29]), "+f"(d[30]), "+f"(d[31])
        : "r"(a0), "r"(a1), "r"(a2), "r"(a3), "l"(db), "r"(scale_d));
}
template <int N>
__device__ __forceinline__ void wgmma_n72_rs_tb(float (&d)[N], uint32_t a0, uint32_t a1, uint32_t a2, uint32_t a3, uint64_t db, int scale_d) {
    asm volatile("{\n.reg .pred p;\nsetp.ne.b32 p, %41, 0;\n"
        "wgmma.mma_async.sync.aligned.m64n72k16.f32.bf16.bf16 "
        "{%0, %1, %2, %3, %4, %5, %6, %7, %8, %9, %10, %11, %12, %13, %14, %15, "
        "%16, %17, %18, %19, %20, %21, %22, %23, %24, %25, %26, %27, %28, %29, %30, %31, "
        "%32, %33, %34, %35}, "
        "{%36, %37, %38, %39}, %40, p, 1, 1, 1;\n}\n"
        : "+f"(d[0]), "+f"(d[1]), "+f"(d[2]), "+f"(d[3]), "+f"(d[4]), "+f"(d[5]), "+f"(d[6]), "+f"(d[7]),
          "+f"(d[8]), "+f"(d[9]), "+f"(d[10]), "+f"(d[11]), "+f"(d[12]), "+f"(d[13]), "+f"(d[14]), "+f"(d[15]),
          "+f"(d[16]), "+f"(d[17]), "+f"(d[18]), "+f"(d[19]), "+f"(d[20]), "+f"(d[21]), "+f"(d[22]), "+f"(d[23]),
          "+f"(d[24]), "+f"(d[25]), "+f"(d[26]), "+f"(d[27]), "+f"(d[28]), "+f"(d[29]), "+f"(d[30]), "+f"(d[31]),
          "+f"(d[32]), "+f"(d[33]), "+f"(d[34]), "+f"(d[35])
        : "r"(a0), "r"(a1), "r"(a2), "r"(a3), "l"(db), "r"(scale_d));
}
template <int N>
__device__ __forceinline__ void wgmma_n128_rs(float (&d)[N], uint32_t a0, uint32_t a1, uint32_t a2, uint32_t a3, uint64_t db, int scale_d) {
    asm volatile("{\n.reg .pred p;\nsetp.ne.b32 p, %69, 0;\n"
        "wgmma.mma_async.sync.aligned.m64n128k16.f32.bf16.bf16 "
        "{%0, %1, %2, %3, %4, %5, %6, %7, %8, %9, %10, %11, %12, %13, %14, %15, "
        "%16, %17, %18, %19, %20, %21, %22, %23, %24, %25, %26, %27, %28, %29, %30, %31, "
        "%32, %33, %34, %35, %36, %37, %38, %39, %40, %41, %42, %43, %44, %45, %46, %47, "
        "%48, %49, %50, %51, %52, %53, %54, %55, %56, %57, %58, %59, %60, %61, %62, %63}, "
        "{%64, %65, %66, %67}, %68, p, 1, 1, 0;\n}\n"
        : "+f"(d[0]), "+f"(d[1]), "+f"(d[2]), "+f"(d[3]), "+f"(d[4]), "+f"(d[5]), "+f"(d[6]), "+f"(d[7]),
          "+f"(d[8]), "+f"(d[9]), "+f"(d[10]), "+f"(d[11]), "+f"(d[12]), "+f"(d[13]), "+f"(d[14]), "+f"(d[15]),
          "+f"(d[16]), "+f"(d[17]), "+f"(d[18]), "+f"(d[19]), "+f"(d[20]), "+f"(d[21]), "+f"(d[22]), "+f"(d[23]),
          "+f"(d[24]), "+f"(d[25]), "+f"(d[26]), "+f"(d[27]), "+f"(d[28]), "+f"(d[29]), "+f"(d[30]), "+f"(d[31]),
          "+f"(d[32]), "+f"(d[33]), "+f"(d[34]), "+f"(d[35]), "+f"(d[36]), "+f"(d[37]), "+f"(d[38]), "+f"(d[39]),
          "+f"(d[40]), "+f"(d[41]), "+f"(d[42]), "+f"(d[43]), "+f"(d[44]), "+f"(d[45]), "+f"(d[46]), "+f"(d[47]),
          "+f"(d[48]), "+f"(d[49]), "+f"(d[50]), "+f"(d[51]), "+f"(d[52]), "+f"(d[53]), "+f"(d[54]), "+f"(d[55]),
          "+f"(d[56]), "+f"(d[57]), "+f"(d[58]), "+f"(d[59]), "+f"(d[60]), "+f"(d[61]), "+f"(d[62]), "+f"(d[63])
        : "r"(a0), "r"(a1), "r"(a2), "r"(a3), "l"(db), "r"(scale_d));
}
template <int N>
__device__ __forceinline__ void wgmma_n128_ss(float (&d)[N], uint64_t da, uint64_t db, int scale_d) {
    asm volatile("{\n.reg .pred p;\nsetp.ne.b32 p, %66, 0;\n"
        "wgmma.mma_async.sync.aligned.m64n128k16.f32.bf16.bf16 "
        "{%0, %1, %2, %3, %4, %5, %6, %7, %8, %9, %10, %11, %12, %13, %14, %15, "
        "%16, %17, %18, %19, %20, %21, %22, %23, %24, %25, %26, %27, %28, %29, %30, %31, "
        "%32, %33, %34, %35, %36, %37, %38, %39, %40, %41, %42, %43, %44, %45, %46, %47, "
        "%48, %49, %50, %51, %52, %53, %54, %55, %56, %57, %58, %59, %60, %61, %62, %63}, "
        "%64, %65, p, 1, 1, 0, 0;\n}\n"
        : "+f"(d[0]), "+f"(d[1]), "+f"(d[2]), "+f"(d[3]), "+f"(d[4]), "+f"(d[5]), "+f"(d[6]), "+f"(d[7]),
          "+f"(d[8]), "+f"(d[9]), "+f"(d[10]), "+f"(d[11]), "+f"(d[12]), "+f"(d[13]), "+f"(d[14]), "+f"(d[15]),
          "+f"(d[16]), "+f"(d[17]), "+f"(d[18]), "+f"(d[19]), "+f"(d[20]), "+f"(d[21]), "+f"(d[22]), "+f"(d[23]),
          "+f"(d[24]), "+f"(d[25]), "+f"(d[26]), "+f"(d[27]), "+f"(d[28]), "+f"(d[29]), "+f"(d[30]), "+f"(d[31]),
          "+f"(d[32]), "+f"(d[33]), "+f"(d[34]), "+f"(d[35]), "+f"(d[36]), "+f"(d[37]), "+f"(d[38]), "+f"(d[39]),
          "+f"(d[40]), "+f"(d[41]), "+f"(d[42]), "+f"(d[43]), "+f"(d[44]), "+f"(d[45]), "+f"(d[46]), "+f"(d[47]),
          "+f"(d[48]), "+f"(d[49]), "+f"(d[50]), "+f"(d[51]), "+f"(d[52]), "+f"(d[53]), "+f"(d[54]), "+f"(d[55]),
          "+f"(d[56]), "+f"(d[57]), "+f"(d[58]), "+f"(d[59]), "+f"(d[60]), "+f"(d[61]), "+f"(d[62]), "+f"(d[63])
        : "l"(da), "l"(db), "r"(scale_d));
}
template <int N>
__device__ __forceinline__ void wgmma_n256_rs_tb(float (&d)[N], uint32_t a0, uint32_t a1, uint32_t a2, uint32_t a3, uint64_t db, int scale_d) {
    asm volatile("{\n.reg .pred p;\nsetp.ne.b32 p, %133, 0;\n"
        "wgmma.mma_async.sync.aligned.m64n256k16.f32.bf16.bf16 "
        "{%0, %1, %2, %3, %4, %5, %6, %7, %8, %9, %10, %11, %12, %13, %14, %15, "
        "%16, %17, %18, %19, %20, %21, %22, %23, %24, %25, %26, %27, %28, %29, %30, %31, "
        "%32, %33, %34, %35, %36, %37, %38, %39, %40, %41, %42, %43, %44, %45, %46, %47, "
        "%48, %49, %50, %51, %52, %53, %54, %55, %56, %57, %58, %59, %60, %61, %62, %63, "
        "%64, %65, %66, %67, %68, %69, %70, %71, %72, %73, %74, %75, %76, %77, %78, %79, "
        "%80, %81, %82, %83, %84, %85, %86, %87, %88, %89, %90, %91, %92, %93, %94, %95, "
        "%96, %97, %98, %99, %100, %101, %102, %103, %104, %105, %106, %107, %108, %109, %110, %111, "
        "%112, %113, %114, %115, %116, %117, %118, %119, %120, %121, %122, %123, %124, %125, %126, %127}, "
        "{%128, %129, %130, %131}, %132, p, 1, 1, 1;\n}\n"
        : "+f"(d[0]), "+f"(d[1]), "+f"(d[2]), "+f"(d[3]), "+f"(d[4]), "+f"(d[5]), "+f"(d[6]), "+f"(d[7]),
          "+f"(d[8]), "+f"(d[9]), "+f"(d[10]), "+f"(d[11]), "+f"(d[12]), "+f"(d[13]), "+f"(d[14]), "+f"(d[15]),
          "+f"(d[16]), "+f"(d[17]), "+f"(d[18]), "+f"(d[19]), "+f"(d[20]), "+f"(d[21]), "+f"(d[22]), "+f"(d[23]),
          "+f"(d[24]), "+f"(d[25]), "+f"(d[26]), "+f"(d[27]), "+f"(d[28]), "+f"(d[29]), "+f"(d[30]), "+f"(d[31]),
          "+f"(d[32]), "+f"(d[33]), "+f"(d[34]), "+f"(d[35]), "+f"(d[36]), "+f"(d[37]), "+f"(d[38]), "+f"(d[39]),
          "+f"(d[40]), "+f"(d[41]), "+f"(d[42]), "+f"(d[43]), "+f"(d[44]), "+f"(d[45]), "+f"(d[46]), "+f"(d[47]),
          "+f"(d[48]), "+f"(d[49]), "+f"(d[50]), "+f"(d[51]), "+f"(d[52]), "+f"(d[53]), "+f"(d[54]), "+f"(d[55]),
          "+f"(d[56]), "+f"(d[57]), "+f"(d[58]), "+f"(d[59]), "+f"(d[60]), "+f"(d[61]), "+f"(d[62]), "+f"(d[63]),
          "+f"(d[64]), "+f"(d[65]), "+f"(d[66]), "+f"(d[67]), "+f"(d[68]), "+f"(d[69]), "+f"(d[70]), "+f"(d[71]),
          "+f"(d[72]), "+f"(d[73]), "+f"(d[74]), "+f"(d[75]), "+f"(d[76]), "+f"(d[77]), "+f"(d[78]), "+f"(d[79]),
          "+f"(d[80]), "+f"(d[81]), "+f"(d[82]), "+f"(d[83]), "+f"(d[84]), "+f"(d[85]), "+f"(d[86]), "+f"(d[87]),
          "+f"(d[88]), "+f"(d[89]), "+f"(d[90]), "+f"(d[91]), "+f"(d[92]), "+f"(d[93]), "+f"(d[94]), "+f"(d[95]),
          "+f"(d[96]), "+f"(d[97]), "+f"(d[98]), "+f"(d[99]), "+f"(d[100]), "+f"(d[101]), "+f"(d[102]), "+f"(d[103]),
          "+f"(d[104]), "+f"(d[105]), "+f"(d[106]), "+f"(d[107]), "+f"(d[108]), "+f"(d[109]), "+f"(d[110]), "+f"(d[111]),
          "+f"(d[112]), "+f"(d[113]), "+f"(d[114]), "+f"(d[115]), "+f"(d[116]), "+f"(d[117]), "+f"(d[118]), "+f"(d[119]),
          "+f"(d[120]), "+f"(d[121]), "+f"(d[122]), "+f"(d[123]), "+f"(d[124]), "+f"(d[125]), "+f"(d[126]), "+f"(d[127])
        : "r"(a0), "r"(a1), "r"(a2), "r"(a3), "l"(db), "r"(scale_d));
}

constexpr float kC1 = 0.25f * 1.4426950408889634f;
constexpr float kC2 = -1.4426950408889634f / 32.0f;
constexpr float kC3 = -4.0f;

template <int V> struct Int { static constexpr int value = V; };
__device__ __forceinline__ uint32_t slot_addr(uint32_t sb, int s) { return sb + SM_SLOT + s * SLOT_BYTES; }
__device__ __forceinline__ uint32_t bar_addr(uint32_t sb, int b) { return sb + SM_BAR + b * 8; }

__device__ __forceinline__ void release_pair(uint32_t bar, uint32_t rank, uint32_t count = 1) {
    mbar_arrive_n(bar, rank, count);
    mbar_arrive_n(bar, rank ^ 1, count);
}

__device__ __forceinline__ float row_bias(uint32_t tile, int row, int half) {
    const uint32_t base = tile + half * 16384 + row * 128;
    const uint32_t sw = ((row & 7) ^ (half << 2)) << 4;
    float s0 = 0.f, s1 = 0.f, s2 = 0.f, s3 = 0.f;
#pragma unroll
    for (int bt = 0; bt < 4; bt++) {
        uint32_t x[4][4];
#pragma unroll
        for (int i = 0; i < 4; i++)
            asm volatile("ld.shared.v4.u32 {%0, %1, %2, %3}, [%4];" : "=r"(x[i][0]), "=r"(x[i][1]), "=r"(x[i][2]), "=r"(x[i][3])
                         : "r"(base + (bt >> 1) * 8192 + ((((bt & 1) * 4 + i) << 4) ^ sw)));
#pragma unroll
        for (int i = 0; i < 4; i++) {
            float a;
            a = __uint_as_float(x[i][0] << 16); s0 = fmaf(a, a, s0);
            a = __uint_as_float(x[i][0] & 0xffff0000u); s1 = fmaf(a, a, s1);
            a = __uint_as_float(x[i][1] << 16); s2 = fmaf(a, a, s2);
            a = __uint_as_float(x[i][1] & 0xffff0000u); s3 = fmaf(a, a, s3);
            a = __uint_as_float(x[i][2] << 16); s0 = fmaf(a, a, s0);
            a = __uint_as_float(x[i][2] & 0xffff0000u); s1 = fmaf(a, a, s1);
            a = __uint_as_float(x[i][3] << 16); s2 = fmaf(a, a, s2);
            a = __uint_as_float(x[i][3] & 0xffff0000u); s3 = fmaf(a, a, s3);
        }
    }
    float s = (s0 + s1) + (s2 + s3);
    s += __shfl_xor_sync(0xffffffffu, s, 1);
    return fmaf(s, kC2, kC3);
}
__device__ __forceinline__ void st_async_f32(uint32_t addr, float v, uint32_t bar, uint32_t cta) {
    asm volatile("{\n.reg .b32 ra, rb;\nmapa.shared::cluster.u32 ra, %0, %3;\nmapa.shared::cluster.u32 rb, %2, %3;\n"
                 "st.async.weak.shared::cluster.mbarrier::complete_tx::bytes.f32 [ra], %1, [rb];\n}"
                 :: "r"(addr), "f"(v), "r"(bar), "r"(cta) : "memory");
}

__device__ __forceinline__ void load_q_frags(uint32_t (&f)[64], float& qb0, float& qb1, uint32_t tile, int wq, int lane) {
    const int row = wq * 16 + (lane & 7) + ((lane >> 3) & 1) * 8;
    const uint32_t base = tile + row * 128;
#pragma unroll
    for (int k = 0; k < 16; k++) {
        const int chunk = 2 * k + (lane >> 4);
        asm volatile("ldmatrix.sync.aligned.m8n8.x4.shared.b16 {%0, %1, %2, %3}, [%4];"
                     : "=r"(f[4 * k]), "=r"(f[4 * k + 1]), "=r"(f[4 * k + 2]), "=r"(f[4 * k + 3])
                     : "r"(base + (k >> 2) * 8192 + (((chunk & 7) ^ (row & 7)) << 4)));
    }
    float s0 = 0.f, s1 = 0.f, s2 = 0.f, s3 = 0.f;
#pragma unroll
    for (int k = 0; k < 32; k++) {
        float a;
        a = __uint_as_float(f[2 * k] << 16); s0 = fmaf(a, a, s0);
        a = __uint_as_float(f[2 * k] & 0xffff0000u); s1 = fmaf(a, a, s1);
        a = __uint_as_float(f[2 * k + 1] << 16); s2 = fmaf(a, a, s2);
        a = __uint_as_float(f[2 * k + 1] & 0xffff0000u); s3 = fmaf(a, a, s3);
    }
    s0 += s1; s2 += s3;
    s0 += __shfl_xor_sync(0xffffffffu, s0, 1); s2 += __shfl_xor_sync(0xffffffffu, s2, 1);
    s0 += __shfl_xor_sync(0xffffffffu, s0, 2); s2 += __shfl_xor_sync(0xffffffffu, s2, 2);
    qb0 = fmaf(s0, kC2, kC3);
    qb1 = fmaf(s2, kC2, kC3);
}
__device__ __forceinline__ void gemm3(float (&d)[64], const uint32_t (&f)[64], uint32_t b01, uint32_t b23) {
    const uint64_t d0 = desc_sw128(b01, 16), d1 = desc_sw128(b23, 16);
    wg_fence();
#pragma unroll
    for (int k = 0; k < 16; k++)
        wgmma_n128_rs(d, f[4 * k], f[4 * k + 1], f[4 * k + 2], f[4 * k + 3],
                      (k < 8 ? d0 : d1) + ((((k >> 2) & 1) * 16384 + (k & 3) * 32) >> 4), k > 0);
    wg_commit();
}
template <int K0>
__device__ __forceinline__ void gemm3_ss(float (&d)[64], uint32_t qs, uint32_t pb) {
    const uint64_t da = desc_sw128(qs + (K0 >> 2) * 8192, 16), db = desc_sw128(pb, 16);
#pragma unroll
    for (int k = 0; k < 8; k++)
        wgmma_n128_ss(d, da + (((k >> 2) * 8192 + (k & 3) * 32) >> 4), db + (((k >> 2) * 16384 + (k & 3) * 32) >> 4), (K0 + k) > 0);
}
template <int K0>
__device__ __forceinline__ void tile_sumsq(float& s0, float& s1, uint32_t tile, int wq, int lane) {
    const int row = wq * 16 + (lane & 7) + ((lane >> 3) & 1) * 8;
    const uint32_t base = tile + row * 128;
    float t0 = 0.f, t1 = 0.f;
#pragma unroll
    for (int kb = 0; kb < 2; kb++) {
        uint32_t x[4][4];
#pragma unroll
        for (int i = 0; i < 4; i++) {
            const int k = K0 + kb * 4 + i, chunk = 2 * k + (lane >> 4);
            asm volatile("ldmatrix.sync.aligned.m8n8.x4.shared.b16 {%0, %1, %2, %3}, [%4];"
                         : "=r"(x[i][0]), "=r"(x[i][1]), "=r"(x[i][2]), "=r"(x[i][3])
                         : "r"(base + (k >> 2) * 8192 + (((chunk & 7) ^ (row & 7)) << 4)));
        }
#pragma unroll
        for (int i = 0; i < 4; i++) {
            float a;
            a = __uint_as_float(x[i][0] << 16); s0 = fmaf(a, a, s0);
            a = __uint_as_float(x[i][0] & 0xffff0000u); t0 = fmaf(a, a, t0);
            a = __uint_as_float(x[i][1] << 16); s1 = fmaf(a, a, s1);
            a = __uint_as_float(x[i][1] & 0xffff0000u); t1 = fmaf(a, a, t1);
            a = __uint_as_float(x[i][2] << 16); s0 = fmaf(a, a, s0);
            a = __uint_as_float(x[i][2] & 0xffff0000u); t0 = fmaf(a, a, t0);
            a = __uint_as_float(x[i][3] << 16); s1 = fmaf(a, a, s1);
            a = __uint_as_float(x[i][3] & 0xffff0000u); t1 = fmaf(a, a, t1);
        }
    }
    s0 += t0;
    s1 += t1;
}
__device__ __forceinline__ void pin_after(float& a, float& b, uint32_t token, uint32_t zero) {
    a = __uint_as_float(__float_as_uint(a) ^ (token & zero));
    b = __uint_as_float(__float_as_uint(b) ^ (token & zero));
}
template <int O>
__device__ __forceinline__ void exp_to_regs(uint32_t (&phi)[64], const float (&a)[64], float qb0, float qb1) {
#pragma unroll
    for (int j = 0; j < 16; j++) {
        phi[O + 2 * j] = pack_bf16(ex2(fmaf(a[4 * j], kC1, qb0)), ex2(fmaf(a[4 * j + 1], kC1, qb0)));
        phi[O + 2 * j + 1] = pack_bf16(ex2(fmaf(a[4 * j + 2], kC1, qb1)), ex2(fmaf(a[4 * j + 3], kC1, qb1)));
    }
}
template <int ID> __device__ __forceinline__ void bar_sync() { asm volatile("bar.sync %0, 256;" :: "n"(ID) : "memory"); }
template <int ID> __device__ __forceinline__ void bar_arrive() { asm volatile("bar.arrive %0, 256;" :: "n"(ID) : "memory"); }

template <int N>
__device__ __forceinline__ void store_out(const float (&o)[N], float inv0, float inv1, __nv_bfloat16* p0) {
#pragma unroll
    for (int t = 0; t < 2; t++) {
#pragma unroll
        for (int i = 0; i < 2; i++) {
            const float inv = i ? inv1 : inv0;
            uint4 v;
            v.x = pack_bf16(o[16 * t + 2 * i] * inv, o[16 * t + 2 * i + 1] * inv);
            v.y = pack_bf16(o[16 * t + 4 + 2 * i] * inv, o[16 * t + 4 + 2 * i + 1] * inv);
            v.z = pack_bf16(o[16 * t + 8 + 2 * i] * inv, o[16 * t + 8 + 2 * i + 1] * inv);
            v.w = pack_bf16(o[16 * t + 12 + 2 * i] * inv, o[16 * t + 12 + 2 * i + 1] * inv);
            *reinterpret_cast<uint4*>(p0 + i * 8 * kDim + t * 32) = v;
        }
    }
}

__global__ void __cluster_dims__(2, 1, 1) __launch_bounds__(384, 1)
performer_kernel(const __grid_constant__ CUtensorMap tm_q, const __grid_constant__ CUtensorMap tm_k,
                 const __grid_constant__ CUtensorMap tm_v, const __grid_constant__ CUtensorMap tm_p,
                 const uint8_t* __restrict__ kptr, const uint8_t* __restrict__ pptr, __nv_bfloat16* __restrict__ out) {
    extern __shared__ __align__(1024) uint8_t smem[];
    const uint32_t sb = (uint32_t)__cvta_generic_to_shared(smem);
    const int tid = threadIdx.x, lane = tid & 31;
    const int warp = __shfl_sync(0xffffffffu, tid >> 5, 0);
    uint32_t rank;
    asm volatile("mov.u32 %0, %%cluster_ctarank;" : "=r"(rank));
    const int cta = blockIdx.x, pair = cta >> 1, h = pair >> 2, sc = pair & 3;

    if (tid == 64) {
        asm volatile("cp.async.bulk.prefetch.L2.global [%0], %1;"
                     :: "l"(kptr + (size_t)(h * kSeq + sc * 512 + rank * 32) * 512), "r"(16384) : "memory");
        asm volatile("cp.async.bulk.prefetch.L2.global [%0], %1;" :: "l"(pptr + cta * 1024), "r"(1024) : "memory");
    }
    if (tid == 32) {
        asm volatile("prefetch.tensormap [%0];" :: "l"(&tm_k) : "memory");
        asm volatile("prefetch.tensormap [%0];" :: "l"(&tm_p) : "memory");
        asm volatile("prefetch.tensormap [%0];" :: "l"(&tm_v) : "memory");
        asm volatile("prefetch.tensormap [%0];" :: "l"(&tm_q) : "memory");
    }
    if (tid == 0) {
        PROF(0);
        mbar_init(bar_addr(sb, B_PROJ), 1);
#pragma unroll
        for (int i = 0; i < 5; i++) { mbar_init(bar_addr(sb, B_FULL + i), 1); mbar_init(bar_addr(sb, B_EMPTY + i), 20); }
#pragma unroll
        for (int i = 0; i < 4; i++) { mbar_init(bar_addr(sb, B_KV + i), 1); mbar_init(bar_addr(sb, B_NORM + i), 1); }
#pragma unroll
        for (int i = 0; i < 2; i++) { mbar_init(bar_addr(sb, B_SFREE + i), 1); mbar_init(bar_addr(sb, B_ACONS + i), 4); }
#pragma unroll
        for (int i = 0; i < 2; i++) mbar_init(bar_addr(sb, B_STG + i), 8);
        mbar_init(bar_addr(sb, B_DUMPED), 1);
        mbar_init(bar_addr(sb, B_PO01), 1);
        mbar_init(bar_addr(sb, B_PO23), 1);
        mbar_init(bar_addr(sb, B_ZERO), 1);
        mbar_init(bar_addr(sb, B_PDEAD), 8);
        mbar_init(bar_addr(sb, B_P0DEAD), 8);
        mbar_init(bar_addr(sb, B_B0DEAD), 4);
        mbar_init(bar_addr(sb, B_KSUM), 1);
        mbar_init(bar_addr(sb, B_GO), 1);
        mbar_init(bar_addr(sb, B_QARR), 1);
        asm volatile("fence.mbarrier_init.release.cluster;" ::: "memory");
    }
    __syncwarp();
    asm volatile("barrier.cluster.arrive.relaxed.aligned;" ::: "memory");
    asm volatile("barrier.cluster.wait.aligned;" ::: "memory");
    if (tid == 0) {
        const int row0 = h * kSeq + sc * 512;
        const uint64_t pol = policy_evict_first();
        mbar_expect_tx(bar_addr(sb, B_FULL + 0), SLOT_BYTES);
        tma_load_mc(slot_addr(sb, 0) + rank * 16384, &tm_k, bar_addr(sb, B_FULL + 0), row0, rank * 2, pol);
        mbar_expect_tx(bar_addr(sb, B_PROJ), 65536);
        tma_load(sb + SM_P0, &tm_p, bar_addr(sb, B_PROJ), rank * 128, 0);
        tma_load(sb + SM_P0 + 32768, &tm_p, bar_addr(sb, B_PROJ), rank * 128, 2);
        mbar_expect_tx(bar_addr(sb, B_FULL + 1), SLOT_BYTES);
        tma_load_mc(slot_addr(sb, 1) + rank * 16384, &tm_v, bar_addr(sb, B_FULL + 1), row0, rank * 2, pol);
        mbar_expect_tx(bar_addr(sb, B_FULL + 2), SLOT_BYTES);
        tma_load_mc(slot_addr(sb, 2) + rank * 16384, &tm_k, bar_addr(sb, B_FULL + 2), row0 + 64, rank * 2, pol);
    }
    __syncwarp();

    if (warp < 4) {
        reg_dealloc<40>();
        if (warp == 0) {
            if (lane == 0) {
                const int row0 = h * kSeq + sc * 512;
                const uint64_t pol = policy_evict_first();
                auto load_item = [&](int i) {
                    const int s = i % 5;
                    if (i >= 5) mbar_wait(bar_addr(sb, B_EMPTY + s), (i / 5 - 1) & 1);
                    mbar_expect_tx(bar_addr(sb, B_FULL + s), SLOT_BYTES);
                    tma_load_mc(slot_addr(sb, s) + rank * 16384, (i & 1) ? &tm_v : &tm_k, bar_addr(sb, B_FULL + s),
                                row0 + (i >> 1) * 64, rank * 2, pol);
                };
                PROFS(1);
                mbar_wait(bar_addr(sb, B_FULL + 0), 0);
                PROFS(3);
                load_item(3);
                mbar_wait(bar_addr(sb, B_FULL + 1), 0);
                load_item(4);
#pragma unroll 1
                for (int i = 5; i < 16; i++) {
                    load_item(i);
                    if (i == 6) mbar_arrive(bar_addr(sb, B_GO));
                }
                CLKP(0);
                const int qrow = row0 + rank * 256;
                auto load_q = [&](int piece, int slot) {
                    mbar_expect_tx(bar_addr(sb, B_FULL + slot), SLOT_BYTES);
                    tma_load_ef(slot_addr(sb, slot), &tm_q, bar_addr(sb, B_FULL + slot), qrow + piece * 64, 0, pol);
                    tma_load_ef(slot_addr(sb, slot) + 16384, &tm_q, bar_addr(sb, B_FULL + slot), qrow + piece * 64, 2, pol);
                };
                mbar_wait(bar_addr(sb, B_EMPTY + 1), 0);
                load_q(0, S_QA);
                mbar_wait(bar_addr(sb, B_EMPTY + 2), 0);
                mbar_expect_tx(bar_addr(sb, B_PO23), SLOT_BYTES);
                tma_load(slot_addr(sb, S_PO23), &tm_p, bar_addr(sb, B_PO23), (rank ^ 1) * 128, 2);
                CLKP(1);
                mbar_wait(bar_addr(sb, B_EMPTY + 3), 0);
                CLKP(3);
                mbar_expect_tx(bar_addr(sb, B_PO01), SLOT_BYTES);
                tma_load(slot_addr(sb, S_PO01), &tm_p, bar_addr(sb, B_PO01), (rank ^ 1) * 128, 0);
                mbar_wait(bar_addr(sb, B_EMPTY + 4), 0);
                load_q(1, S_QB);
                CLKP(4);
                mbar_wait(bar_addr(sb, B_ACONS + 0), 0);
                load_q(2, S_QA);
                CLKP(7);
                mbar_wait(bar_addr(sb, B_ACONS + 1), 0);
                load_q(3, S_QB);
                CLKP(8);
                mbar_wait(bar_addr(sb, B_FULL + S_QB), 0);
                mbar_arrive(bar_addr(sb, B_QARR));
            }
            __syncwarp();
        } else if (warp < 3) {
            const int w = warp - 1;
            const int row = rank * 32 + w * 16 + (lane >> 1);
            int s = 0, ph = 0;
#pragma unroll 1
            for (int t = 0; t < 8; t++) {
                const uint32_t nbar = bar_addr(sb, B_NORM + (t & 3));
                if (w == 0 && lane == 0) mbar_expect_tx(nbar, 256);
                mbar_wait(bar_addr(sb, B_FULL + s), ph);
                const float b = row_bias(slot_addr(sb, s), row, lane & 1);
                if (!(lane & 1)) {
                    const uint32_t dst = sb + SM_NORM + (t & 3) * 256 + row * 4;
                    st_async_f32(dst, b, nbar, 0);
                    st_async_f32(dst, b, nbar, 1);
                }
                __syncwarp();
                if (lane == 0) release_pair(bar_addr(sb, B_EMPTY + s), rank);
                s += 2;
                if (s >= 5) { s -= 5; ph ^= 1; }
            }
            if (w == 0 && lane == 0) {
                const uint32_t src = slot_addr(sb, S_STG);
                mbar_wait(bar_addr(sb, B_ZERO), 0);
#pragma unroll 1
                for (int r = 0; r < 2; r++) {
                    mbar_wait(bar_addr(sb, B_STG + r), 0);
                    if (r == 1) mbar_wait(bar_addr(sb, B_QARR), 0);
                    CLKP(17 + r);
                    asm volatile("fence.proxy.async.global;" ::: "memory");
                    if (r == 0)
                        asm volatile("cp.reduce.async.bulk.global.shared::cta.bulk_group.add.f32 [%0], [%1], %2;"
                                     :: "l"(g_ksum + h * 256 + rank * 128), "r"(sb + SM_KS), "r"(512) : "memory");
#pragma unroll 1
                    for (int b = 0; b < 8; b++) {
                        const int g2 = b >> 2, u = (b >> 1) & 1, hf = b & 1;
                        uint8_t* dst = reinterpret_cast<uint8_t*>(g_kvacc + h * 8192) + (2 * r + u) * 32768 + (rank * 128 + g2 * 64 + hf * 32) * 128;
                        asm volatile("cp.reduce.async.bulk.global.shared::cta.bulk_group.add.noftz.bf16 [%0], [%1], %2;"
                                     :: "l"(dst), "r"(src + b * 4096), "r"(4096) : "memory");
                        asm volatile("cp.async.bulk.commit_group;" ::: "memory");
                        asm volatile("cp.async.bulk.wait_group.read 0;" ::: "memory");
                    }
                    mbar_arrive(bar_addr(sb, B_SFREE + r));
                    CLKP(9 + r);
                    asm volatile("cp.async.bulk.wait_group 0;" ::: "memory");
                    asm volatile("fence.proxy.async.global;" ::: "memory");
                    red_add_u32(&g_flag_dump[h * 64 + r * 32], 1);
                    if (r == 0) mbar_arrive(bar_addr(sb, B_DUMPED));
                    CLKP(12 + 2 * r);
                }
            }
            __syncwarp();
        } else {
            unsigned target = 0;
            if (lane == 0) target = ld_relaxed_gpu(&g_flag_dump[h * 64 + 32]) + 8;
            mbar_wait(bar_addr(sb, B_GO), 0);
            uint4* z = g_kvacc + h * 8192 + (cta & 7) * 1024;
#pragma unroll 4
            for (int i = 0; i < 32; i++) z[i * 32 + lane] = make_uint4(0, 0, 0, 0);
            g_ksum[h * 256 + (cta & 7) * 32 + lane] = 0.f;
            __syncwarp();
            if (lane == 0) {
                fence_gpu();
                red_add_u32(&g_flag_zero[h * 32], 1);
                spin_flag(&g_flag_zero[h * 32], target);
                asm volatile("fence.proxy.async.global;" ::: "memory");
                mbar_arrive(bar_addr(sb, B_ZERO));
                mbar_wait(bar_addr(sb, B_DUMPED), 0);
                spin_flag(&g_flag_dump[h * 64], target);
                asm volatile("fence.proxy.async.global;" ::: "memory");
                CLKP(15);
            }
            __syncwarp();
            float kv8[8];
#pragma unroll
            for (int i = 0; i < 8; i++) kv8[i] = __ldcg(g_ksum + h * 256 + i * 32 + lane);
            const uint8_t* kvsrc = reinterpret_cast<const uint8_t*>(g_kvacc + h * 8192);
            if (lane == 0) {
                mbar_wait(bar_addr(sb, B_P0DEAD), 0);
                mbar_expect_tx(bar_addr(sb, B_KV + 0), SLOT_BYTES);
                bulk_load(sb + SM_P0, kvsrc, SLOT_BYTES, bar_addr(sb, B_KV + 0));
                mbar_expect_tx(bar_addr(sb, B_KV + 1), SLOT_BYTES);
                bulk_load(sb + SM_P0 + 32768, kvsrc + 32768, SLOT_BYTES, bar_addr(sb, B_KV + 1));
            }
            __syncwarp();
            if (lane == 0) CLKP(5);
            mbar_wait(bar_addr(sb, B_B0DEAD), 0);
            if (lane == 0) CLKP(6);
#pragma unroll
            for (int i = 0; i < 8; i++) {
                const int m = i * 32 + lane;
                asm volatile("st.shared.v4.u32 [%0], {%1, %1, %1, %1};" :: "r"(slot_addr(sb, S_QA) + m * 128 + ((m & 7) << 4)), "r"(pack_bf16(kv8[i], kv8[i])) : "memory");
            }
            if (lane == 0) CLKP(11);
            asm volatile("fence.proxy.async.shared::cta;" ::: "memory");
            __syncwarp();
            if (lane == 0) {
                mbar_arrive(bar_addr(sb, B_KSUM));
                CLKP(16);
                spin_flag(&g_flag_dump[h * 64 + 32], target);
                asm volatile("fence.proxy.async.global;" ::: "memory");
                mbar_wait(bar_addr(sb, B_SFREE + 1), 0);
                mbar_expect_tx(bar_addr(sb, B_KV + 2), SLOT_BYTES);
                bulk_load(slot_addr(sb, S_STG), kvsrc + 65536, SLOT_BYTES, bar_addr(sb, B_KV + 2));
                mbar_wait(bar_addr(sb, B_PDEAD), 0);
                mbar_expect_tx(bar_addr(sb, B_KV + 3), SLOT_BYTES);
                bulk_load(slot_addr(sb, S_PO01), kvsrc + 98304, SLOT_BYTES, bar_addr(sb, B_KV + 3));
            }
            __syncwarp();
        }
        asm volatile("barrier.cluster.arrive.relaxed.aligned;" ::: "memory");
        asm volatile("barrier.cluster.wait.aligned;" ::: "memory");
    } else {
        reg_alloc<232>();
        const int w = (warp - 4) >> 2, wq = warp & 3, g = lane >> 2, c = lane & 3;
        float ks0 = 0.f, ks1 = 0.f, qb0, qb1;
        uint32_t f[64], pk[64];
        auto stage = [&](auto round) {
            constexpr int R = decltype(round)::value;
            const uint32_t stg = slot_addr(sb, S_STG) + w * 16384 + (wq * 16 + g) * 128;
            const bool odd = g & 1;
            const uint32_t o0 = (((odd ? 4 : 0) + c) ^ g) << 4, o1 = (((odd ? 0 : 4) + c) ^ g) << 4;
#pragma unroll
            for (int u = 0; u < 2; u++)
#pragma unroll
                for (int i = 0; i < 2; i++) {
                    const uint32_t* e = pk + 16 * (2 * R + u) + 4 * i;
                    asm volatile("st.shared.v4.u32 [%0], {%1, %2, %3, %4};" :: "r"(stg + u * 8192 + i * 1024 + o0),
                                 "r"(odd ? e[8] : e[0]), "r"(odd ? e[9] : e[1]), "r"(odd ? e[10] : e[2]), "r"(odd ? e[11] : e[3]) : "memory");
                    asm volatile("st.shared.v4.u32 [%0], {%1, %2, %3, %4};" :: "r"(stg + u * 8192 + i * 1024 + o1),
                                 "r"(odd ? e[0] : e[8]), "r"(odd ? e[1] : e[9]), "r"(odd ? e[2] : e[10]), "r"(odd ? e[3] : e[11]) : "memory");
                }
            asm volatile("fence.proxy.async.shared::cta;" ::: "memory");
            __syncwarp();
            if (lane == 0) mbar_arrive(bar_addr(sb, B_STG + R));
        };
        {
            float acc[128];
            uint32_t p[16];
            const uint64_t dp = desc_sw128(sb + SM_P0 + w * 8192, 16);
            mbar_wait(bar_addr(sb, B_PROJ), 0);
            PROFA(0); CLKS(28);
            uint32_t pf[4 * kG1Rs];
            {
                const int row = w * 64 + wq * 16 + (lane & 7) + ((lane >> 3) & 1) * 8;
#pragma unroll
                for (int k = 0; k < kG1Rs; k++) {
                    const int chunk = 2 * k + (lane >> 4);
                    asm volatile("ldmatrix.sync.aligned.m8n8.x4.shared.b16 {%0, %1, %2, %3}, [%4];"
                                 : "=r"(pf[4 * k]), "=r"(pf[4 * k + 1]), "=r"(pf[4 * k + 2]), "=r"(pf[4 * k + 3])
                                 : "r"(sb + SM_P0 + (k >> 2) * 16384 + row * 128 + (((chunk & 7) ^ (row & 7)) << 4)));
                }
            }
            int ks = 0, kph = 0;
#pragma unroll 1
            for (int t = 0; t < 8; t++) {
                float s[32];
                const int vs = ks == 0 ? 4 : ks - 1, vph = ks == 0 ? kph ^ 1 : kph;
                CLK(0);
                if (w == 1) bar_sync<2>(); else if (t > 0) bar_sync<3>();
                CLK(1);
                if (t > 0) {
                    mbar_wait(bar_addr(sb, B_FULL + vs), vph);
                    const uint64_t dv = desc_sw128(slot_addr(sb, vs), 8192);
                    wg_fence();
#pragma unroll
                    for (int k = 0; k < 4; k++)
                        wgmma_n256_rs_tb(acc, p[4 * k], p[4 * k + 1], p[4 * k + 2], p[4 * k + 3], dv + ((k * 2048) >> 4), (t - 1 + k) > 0);
                    wg_commit();
                }
                CLK(2);
                mbar_wait(bar_addr(sb, B_FULL + ks), kph);
                const uint64_t dk = desc_sw128(slot_addr(sb, ks), 16);
                wg_fence();
#pragma unroll
                for (int k = 0; k < 16; k++) {
                    if (k < kG1Rs)
                        wgmma_n64_rs(s, pf[4 * k], pf[4 * k + 1], pf[4 * k + 2], pf[4 * k + 3], dk + (((k >> 2) * 8192 + (k & 3) * 32) >> 4), k > 0);
                    else
                        wgmma_n64_ss(s, dp + (((k >> 2) * 16384 + (k & 3) * 32) >> 4), dk + (((k >> 2) * 8192 + (k & 3) * 32) >> 4), k > 0);
                }
                wg_commit();
                if (w == 0) bar_arrive<2>(); else bar_arrive<3>();
                CLK(3);
                if (t > 0) {
                    wg_wait<1>();
                    if (lane == 0) release_pair(bar_addr(sb, B_EMPTY + vs), rank, wq == 0 ? 2 : 1);
                }
                CLK(4);
                wg_wait<0>();
                CLK(5);
                CLKALL(t);
                if (lane == 0) release_pair(bar_addr(sb, B_EMPTY + ks), rank);
                mbar_wait(bar_addr(sb, B_NORM + (t & 3)), (t >> 2) & 1);
                CLK(6);
                const uint32_t nb = sb + SM_NORM + (t & 3) * 256 + c * 8;
                float bias[16];
#pragma unroll
                for (int j = 0; j < 8; j++)
                    asm volatile("ld.shared.v2.f32 {%0, %1}, [%2];" : "=f"(bias[2 * j]), "=f"(bias[2 * j + 1]) : "r"(nb + j * 32) : "memory");
#pragma unroll
                for (int j = 0; j < 8; j++) {
                    const float bx = bias[2 * j], by = bias[2 * j + 1];
                    const float p00 = ex2(fmaf(s[4 * j], kC1, bx)), p01 = ex2(fmaf(s[4 * j + 1], kC1, by));
                    const float p10 = ex2(fmaf(s[4 * j + 2], kC1, bx)), p11 = ex2(fmaf(s[4 * j + 3], kC1, by));
                    ks0 += p00 + p01;
                    ks1 += p10 + p11;
                    p[2 * j] = pack_bf16(p00, p01);
                    p[2 * j + 1] = pack_bf16(p10, p11);
                }
                CLK(7);
                ks += 2;
                if (ks >= 5) { ks -= 5; kph ^= 1; }
            }
            if (w == 1) bar_sync<2>(); else bar_sync<3>();
            mbar_wait(bar_addr(sb, B_FULL + 0), 1);
            {
                const uint64_t dv = desc_sw128(slot_addr(sb, 0), 8192);
                wg_fence();
#pragma unroll
                for (int k = 0; k < 4; k++)
                    wgmma_n256_rs_tb(acc, p[4 * k], p[4 * k + 1], p[4 * k + 2], p[4 * k + 3], dv + ((k * 2048) >> 4), 1);
                wg_commit();
            }
            if (w == 0) bar_arrive<2>();
            wg_wait<0>();
            PROFA(6); CLKS(11);
            ks0 += __shfl_xor_sync(0xffffffffu, ks0, 1); ks0 += __shfl_xor_sync(0xffffffffu, ks0, 2);
            ks1 += __shfl_xor_sync(0xffffffffu, ks1, 1); ks1 += __shfl_xor_sync(0xffffffffu, ks1, 2);
            if (c == 0) {
                asm volatile("st.shared.f32 [%0], %1;" :: "r"(sb + SM_KS + (w * 64 + wq * 16 + g) * 4), "f"(ks0) : "memory");
                asm volatile("st.shared.f32 [%0], %1;" :: "r"(sb + SM_KS + (w * 64 + wq * 16 + g + 8) * 4), "f"(ks1) : "memory");
            }
#pragma unroll
            for (int t = 0; t < 8; t++)
#pragma unroll
                for (int i = 0; i < 2; i++)
#pragma unroll
                    for (int jj = 0; jj < 4; jj++)
                        pk[8 * t + 4 * i + jj] = pack_bf16(acc[16 * t + 4 * jj + 2 * i], acc[16 * t + 4 * jj + 2 * i + 1]);
            auto load_a = [&]() {
                mbar_wait(bar_addr(sb, B_FULL + (w == 0 ? S_QA : S_QB)), 1);
                PROFW(8); CLKS(13);
                load_q_frags(f, qb0, qb1, slot_addr(sb, w == 0 ? S_QA : S_QB), wq, lane);
                asm volatile("fence.proxy.async.shared::cta;" ::: "memory");
                __syncwarp();
                if (lane == 0) mbar_arrive(bar_addr(sb, B_ACONS + w));
            };
            bar_sync<3>();
            stage(Int<0>{});
            PROFW(7); CLKS(12);
            load_a();
            PROFW(9); CLKS(14);
        }

        uint32_t phi[64], phib[64];
        const uint32_t qsb = slot_addr(sb, w == 0 ? S_QA : S_QB);
        {
            const uint32_t p0 = sb + SM_P0, po01 = slot_addr(sb, S_PO01), po23 = slot_addr(sb, S_PO23);
            float a[64];
            gemm3(a, f, p0, p0 + 32768);
            PROFW(10); CLKS(15);
            wg_wait<0>();
            PROFW(11); CLKS(16);
            exp_to_regs<0>(phi, a, qb0, qb1);
            PROFW(12); CLKS(17);
            if (w == 1) {
                mbar_wait(bar_addr(sb, B_SFREE + 0), 0);
                stage(Int<1>{});
            }
            mbar_wait(bar_addr(sb, B_PO01), 0);
            mbar_wait(bar_addr(sb, B_PO23), 0);
            PROFW(13); CLKS(18);
            gemm3(a, f, po01, po23);
            PROFW(14); CLKS(19);
            if (w == 0) {
                mbar_wait(bar_addr(sb, B_SFREE + 0), 0);
                stage(Int<1>{});
            }
            wg_wait<0>();
            PROFW(16); CLKS(20);
            exp_to_regs<32>(phi, a, qb0, qb1);
            mbar_wait(bar_addr(sb, B_FULL + (w == 0 ? S_QA : S_QB)), 0);
            PROFW(17); CLKS(21);
            float s0 = 0.f, s1 = 0.f;
            wg_fence();
            gemm3_ss<0>(a, qsb, p0);
            tile_sumsq<0>(s0, s1, qsb, wq, lane);
            gemm3_ss<8>(a, qsb, p0 + 32768);
            wg_commit();
            tile_sumsq<8>(s0, s1, qsb, wq, lane);
            s0 += __shfl_xor_sync(0xffffffffu, s0, 1); s1 += __shfl_xor_sync(0xffffffffu, s1, 1);
            s0 += __shfl_xor_sync(0xffffffffu, s0, 2); s1 += __shfl_xor_sync(0xffffffffu, s1, 2);
            qb0 = fmaf(s0, kC2, kC3);
            qb1 = fmaf(s1, kC2, kC3);
            PROFW(18); CLKS(22);
            wg_wait<0>();
            PROFW(19); CLKS(23);
            pin_after(qb0, qb1, mbar_arrive_lane0(bar_addr(sb, B_P0DEAD), lane), rank >> 8);
            exp_to_regs<0>(phib, a, qb0, qb1);
            wg_fence();
            gemm3_ss<0>(a, qsb, po01);
            gemm3_ss<8>(a, qsb, po23);
            wg_commit();
            wg_wait<0>();
            PROFW(21); CLKS(24);
            if (w == 0 && lane == 0) mbar_arrive(bar_addr(sb, B_B0DEAD));
            pin_after(qb0, qb1, mbar_arrive_lane0(bar_addr(sb, B_PDEAD), lane), rank >> 8);
            exp_to_regs<32>(phib, a, qb0, qb1);
            PROFW(22); CLKS(25);
        }
        asm volatile("barrier.cluster.arrive.relaxed.aligned;" ::: "memory");
        {
            const uint32_t kvb[4] = {sb + SM_P0, sb + SM_P0 + 32768, slot_addr(sb, S_STG), slot_addr(sb, S_PO01)};
            const uint32_t mo = rank * 128 * 128, mx = (rank ^ 1) * 128 * 128;
            const int orow = h * kSeq + sc * 512 + rank * 256 + w * 64 + wq * 16 + g;
            __nv_bfloat16* pA = out + (size_t)orow * kDim + c * 8;
            __nv_bfloat16* pB = pA + 128 * kDim;
            float iA0, iA1, iB0, iB1;
            auto take_turn = [&](bool first) { if (w == 1) bar_sync<2>(); else if (!first) bar_sync<3>(); };
            auto give_turn = [&](bool last) { if (w == 0) bar_arrive<2>(); else if (!last) bar_arrive<3>(); };
            {
                float e[36];
                const uint32_t lbo = slot_addr(sb, S_QA) - kvb[0];
                auto tile0 = [&](const uint32_t (&ph)[64], bool first) {
                    const uint64_t d0 = desc_sw128(kvb[0] + mo, lbo), d1 = desc_sw128(kvb[0] + mx, lbo);
                    take_turn(first);
                    wg_fence();
#pragma unroll
                    for (int k = 0; k < 16; k++)
                        wgmma_n72_rs_tb(e, ph[4 * k], ph[4 * k + 1], ph[4 * k + 2], ph[4 * k + 3], (k < 8 ? d0 : d1) + (((k & 7) * 2048) >> 4), k > 0);
                    wg_commit();
                    give_turn(false);
                    wg_wait<0>();
                };
                mbar_wait(bar_addr(sb, B_KV + 0), 0);
                mbar_wait(bar_addr(sb, B_KSUM), 0);
                PROFA(23); CLKS(26);
                tile0(phi, true);
                iA0 = __fdividef(1.f, e[32] + 1e-6f);
                iA1 = __fdividef(1.f, e[34] + 1e-6f);
                store_out(e, iA0, iA1, pA);
                CLKG4(0);
                tile0(phib, false);
                iB0 = __fdividef(1.f, e[32] + 1e-6f);
                iB1 = __fdividef(1.f, e[34] + 1e-6f);
                store_out(e, iB0, iB1, pB);
                CLKG4(1);
            }
#pragma unroll
            for (int i = 2; i < 8; i++) {
                const int b = i >> 1;
                float o[32];
                const uint64_t d0 = desc_sw128(kvb[b] + mo, 16), d1 = desc_sw128(kvb[b] + mx, 16);
                if (!(i & 1)) mbar_wait(bar_addr(sb, B_KV + b), 0);
                take_turn(false);
                wg_fence();
#pragma unroll
                for (int k = 0; k < 16; k++) {
                    const uint32_t (&ph)[64] = (i & 1) ? phib : phi;
                    wgmma_n64_rs_tb(o, ph[4 * k], ph[4 * k + 1], ph[4 * k + 2], ph[4 * k + 3], (k < 8 ? d0 : d1) + (((k & 7) * 2048) >> 4), k > 0);
                }
                wg_commit();
                give_turn(i == 7);
                wg_wait<0>();
                if (i & 1) store_out(o, iB0, iB1, pB + b * 64); else store_out(o, iA0, iA1, pA + b * 64);
                CLKG4(i);
            }
        }
        PROFA(24);
        CLKS(27);
        asm volatile("barrier.cluster.wait.aligned;" ::: "memory");
    }
}

typedef CUresult (*EncodeTiledFn)(CUtensorMap*, CUtensorMapDataType, cuuint32_t, void*, const cuuint64_t*, const cuuint64_t*,
                                  const cuuint32_t*, const cuuint32_t*, CUtensorMapInterleave, CUtensorMapSwizzle,
                                  CUtensorMapL2promotion, CUtensorMapFloatOOBfill);

bool make_map(EncodeTiledFn enc, CUtensorMap* m, const void* base, uint64_t rows, uint32_t box_rows) {
    cuuint64_t dims[3] = {64, rows, 4};
    cuuint64_t strides[2] = {512, 128};
    cuuint32_t box[3] = {64, box_rows, 2};
    cuuint32_t es[3] = {1, 1, 1};
    return enc(m, CU_TENSOR_MAP_DATA_TYPE_BFLOAT16, 3, const_cast<void*>(base), dims, strides, box, es,
               CU_TENSOR_MAP_INTERLEAVE_NONE, CU_TENSOR_MAP_SWIZZLE_128B, CU_TENSOR_MAP_L2_PROMOTION_L2_256B,
               CU_TENSOR_MAP_FLOAT_OOB_FILL_NONE) == CUDA_SUCCESS;
}

}

extern "C" void kernel_launch(void* const* d_in, const int* in_sizes, int n_in, void* d_out, int out_size) {
    (void)in_sizes; (void)n_in; (void)out_size;
    static EncodeTiledFn enc = nullptr;
    if (!enc) {
        void* fn = nullptr;
        cudaDriverEntryPointQueryResult qr;
        if (cudaGetDriverEntryPoint("cuTensorMapEncodeTiled", &fn, cudaEnableDefault, &qr) != cudaSuccess || !fn) return;
        enc = (EncodeTiledFn)fn;
        cudaFuncSetAttribute(performer_kernel, cudaFuncAttributeMaxDynamicSharedMemorySize, SM_TOTAL);
    }
    CUtensorMap tq, tk, tv, tp;
    if (!make_map(enc, &tq, d_in[0], kHeads * kSeq, 64) || !make_map(enc, &tk, d_in[1], kHeads * kSeq, 64) ||
        !make_map(enc, &tv, d_in[2], kHeads * kSeq, 64) || !make_map(enc, &tp, d_in[3], 256, 128)) return;
    performer_kernel<<<128, 384, SM_TOTAL, cudaStreamPerThread>>>(tq, tk, tv, tp, (const uint8_t*)d_in[1], (const uint8_t*)d_in[3],
                                                                    (__nv_bfloat16*)d_out);
}
```

```cpp
#include <cuda_runtime.h>
#include <cuda_bf16.h>
#include <cuda.h>
#include <stdint.h>

namespace {

constexpr int kHeads = 16;
constexpr int kSeq = 2048;
constexpr int kDim = 256;

constexpr uint32_t SM_P0 = 0;
constexpr uint32_t SM_SLOT = 65536;
constexpr uint32_t SLOT_BYTES = 32768;
constexpr uint32_t SM_BAR = SM_SLOT + 5 * SLOT_BYTES;
constexpr uint32_t SM_NORM = SM_BAR + 512;
constexpr uint32_t SM_KS = SM_NORM + 1024;
constexpr uint32_t SM_TOTAL = SM_KS + 512;

constexpr int S_STG = 0, S_QA = 1, S_PO23 = 2, S_PO01 = 3, S_QB = 4;

constexpr int B_PROJ = 0;
constexpr int B_FULL = 1;
constexpr int B_EMPTY = 6;
constexpr int B_NORM = 11;
constexpr int B_KV = 15;
constexpr int B_STG = 19;
constexpr int B_GO = 21;
constexpr int B_ACONS = 22;
constexpr int B_SFREE = 24;
constexpr int B_PO01 = 26;
constexpr int B_PO23 = 27;
constexpr int B_ZERO = 28;
constexpr int B_PDEAD = 29;
constexpr int B_B0DEAD = 30;
constexpr int B_KSUM = 31;
constexpr int B_DUMPED = 32;
constexpr int B_P0DEAD = 33;
constexpr int B_QARR = 34;

constexpr int kG1Rs = 7;
constexpr int kSpinLimit = 1 << 21;

__device__ uint4 g_kvacc[kHeads * 8192];
__device__ float g_ksum[kHeads * 256];
__device__ unsigned g_flag_zero[kHeads * 32];
__device__ unsigned g_flag_dump[kHeads * 64];

__device__ __forceinline__ void mbar_init(uint32_t bar, uint32_t cnt) {
    asm volatile("mbarrier.init.shared::cta.b64 [%0], %1;" :: "r"(bar), "r"(cnt) : "memory");
}
__device__ __forceinline__ void mbar_expect_tx(uint32_t bar, uint32_t bytes) {
    asm volatile("mbarrier.arrive.expect_tx.shared::cta.b64 _, [%0], %1;" :: "r"(bar), "r"(bytes) : "memory");
}
__device__ __forceinline__ void mbar_arrive(uint32_t bar) {
    asm volatile("mbarrier.arrive.shared::cta.b64 _, [%0];" :: "r"(bar) : "memory");
}
__device__ __forceinline__ uint32_t mbar_arrive_lane0(uint32_t bar, int lane) {
    uint32_t lo;
    asm volatile("{\n.reg .pred p;\n.reg .b64 st;\n.reg .b32 hi;\nmov.b64 st, 0;\nsetp.eq.s32 p, %2, 0;\n"
                 "@p mbarrier.arrive.shared::cta.b64 st, [%1];\nmov.b64 {%0, hi}, st;\n}" : "=r"(lo) : "r"(bar), "r"(lane) : "memory");
    return lo;
}
__device__ __forceinline__ void mbar_arrive_n(uint32_t bar, uint32_t cta, uint32_t count) {
    asm volatile("{\n.reg .b32 ra;\nmapa.shared::cluster.u32 ra, %0, %1;\n"
                 "mbarrier.arrive.shared::cluster.b64 _, [ra], %2;\n}" :: "r"(bar), "r"(cta), "r"(count) : "memory");
}
__device__ __forceinline__ void mbar_wait(uint32_t bar, uint32_t parity) {
    uint32_t ok;
    int it = 0;
    do {
        asm volatile("{\n.reg .pred p;\nmbarrier.try_wait.parity.shared::cta.b64 p, [%1], %2;\nselp.u32 %0, 1, 0, p;\n}"
                     : "=r"(ok) : "r"(bar), "r"(parity) : "memory");
    } while (!ok && ++it < kSpinLimit);
}
__device__ __forceinline__ void tma_load(uint32_t dst, const CUtensorMap* tm, uint32_t bar, int row, int blk) {
    asm volatile("cp.async.bulk.tensor.3d.shared::cluster.global.mbarrier::complete_tx::bytes [%0], [%1, {%3, %4, %5}], [%2];"
                 :: "r"(dst), "l"(tm), "r"(bar), "r"(0), "r"(row), "r"(blk) : "memory");
}
__device__ __forceinline__ uint64_t policy_evict_first() {
    uint64_t p;
    asm volatile("createpolicy.fractional.L2::evict_first.b64 %0, 1.0;" : "=l"(p));
    return p;
}
__device__ __forceinline__ void tma_load_ef(uint32_t dst, const CUtensorMap* tm, uint32_t bar, int row, int blk, uint64_t pol) {
    asm volatile("cp.async.bulk.tensor.3d.shared::cluster.global.mbarrier::complete_tx::bytes.L2::cache_hint [%0], [%1, {%3, %4, %5}], [%2], %6;"
                 :: "r"(dst), "l"(tm), "r"(bar), "r"(0), "r"(row), "r"(blk), "l"(pol) : "memory");
}
__device__ __forceinline__ void tma_load_mc(uint32_t dst, const CUtensorMap* tm, uint32_t bar, int row, int blk, uint64_t pol) {
    asm volatile("cp.async.bulk.tensor.3d.shared::cluster.global.mbarrier::complete_tx::bytes.multicast::cluster.L2::cache_hint [%0], [%1, {%3, %4, %5}], [%2], %6, %7;"
                 :: "r"(dst), "l"(tm), "r"(bar), "r"(0), "r"(row), "r"(blk), "h"((uint16_t)3), "l"(pol) : "memory");
}
__device__ __forceinline__ void bulk_load(uint32_t dst, const void* src, uint32_t bytes, uint32_t bar) {
    asm volatile("cp.async.bulk.shared::cluster.global.mbarrier::complete_tx::bytes [%0], [%1], %2, [%3];"
                 :: "r"(dst), "l"(src), "r"(bytes), "r"(bar) : "memory");
}
__device__ __forceinline__ void wg_fence() { asm volatile("wgmma.fence.sync.aligned;" ::: "memory"); }
__device__ __forceinline__ void wg_commit() { asm volatile("wgmma.commit_group.sync.aligned;" ::: "memory"); }
template <int N> __device__ __forceinline__ void wg_wait() { asm volatile("wgmma.wait_group.sync.aligned %0;" :: "n"(N) : "memory"); }

__device__ __forceinline__ uint64_t desc_sw128(uint32_t addr, uint32_t lbo) {
    asm volatile("" : "+r"(addr));
    return (uint64_t)((addr & 0x3FFFF) >> 4) | ((uint64_t)(lbo >> 4) << 16) | ((uint64_t)(1024 >> 4) << 32) | (1ull << 62);
}
__device__ __forceinline__ uint32_t pack_bf16(float lo, float hi) {
    uint32_t r;
    asm("cvt.rn.bf16x2.f32 %0, %1, %2;" : "=r"(r) : "f"(hi), "f"(lo));
    return r;
}
__device__ __forceinline__ float ex2(float x) {
    float y;
    asm("ex2.approx.ftz.f32 %0, %1;" : "=f"(y) : "f"(x));
    return y;
}
__device__ __forceinline__ unsigned ld_relaxed_gpu(const unsigned* p) {
    unsigned v;
    asm volatile("ld.relaxed.gpu.global.u32 %0, [%1];" : "=r"(v) : "l"(p) : "memory");
    return v;
}
__device__ __forceinline__ void fence_gpu() { asm volatile("fence.acq_rel.gpu;" ::: "memory"); }
__device__ __forceinline__ void red_add_u32(unsigned* p, unsigned v) {
    asm volatile("red.relaxed.gpu.global.add.u32 [%0], %1;" :: "l"(p), "r"(v) : "memory");
}
__device__ __forceinline__ unsigned ld_acquire_gpu(const unsigned* p) {
    unsigned v;
    asm volatile("ld.acquire.gpu.global.u32 %0, [%1];" : "=r"(v) : "l"(p) : "memory");
    return v;
}
__device__ __forceinline__ void spin_flag(const unsigned* p, unsigned target) {
    int it = 0;
    while ((int)(ld_acquire_gpu(p) - target) < 0 && ++it < kSpinLimit) {}
}
template <int R> __device__ __forceinline__ void reg_alloc() { asm volatile("setmaxnreg.inc.sync.aligned.u32 %0;" :: "n"(R)); }
template <int R> __device__ __forceinline__ void reg_dealloc() { asm volatile("setmaxnreg.dec.sync.aligned.u32 %0;" :: "n"(R)); }

template <int N>
__device__ __forceinline__ void wgmma_n64_ss(float (&d)[N], uint64_t da, uint64_t db, int scale_d) {
    asm volatile("{\n.reg .pred p;\nsetp.ne.b32 p, %34, 0;\n"
        "wgmma.mma_async.sync.aligned.m64n64k16.f32.bf16.bf16 "
        "{%0, %1, %2, %3, %4, %5, %6, %7, %8, %9, %10, %11, %12, %13, %14, %15, "
        "%16, %17, %18, %19, %20, %21, %22, %23, %24, %25, %26, %27, %28, %29, %30, %31}, "
        "%32, %33, p, 1, 1, 0, 0;\n}\n"
        : "+f"(d[0]), "+f"(d[1]), "+f"(d[2]), "+f"(d[3]), "+f"(d[4]), "+f"(d[5]), "+f"(d[6]), "+f"(d[7]),
          "+f"(d[8]), "+f"(d[9]), "+f"(d[10]), "+f"(d[11]), "+f"(d[12]), "+f"(d[13]), "+f"(d[14]), "+f"(d[15]),
          "+f"(d[16]), "+f"(d[17]), "+f"(d[18]), "+f"(d[19]), "+f"(d[20]), "+f"(d[21]), "+f"(d[22]), "+f"(d[23]),
          "+f"(d[24]), "+f"(d[25]), "+f"(d[26]), "+f"(d[27]), "+f"(d[28]), "+f"(d[29]), "+f"(d[30]), "+f"(d[31])
        : "l"(da), "l"(db), "r"(scale_d));
}
template <int N>
__device__ __forceinline__ void wgmma_n64_rs(float (&d)[N], uint32_t a0, uint32_t a1, uint32_t a2, uint32_t a3, uint64_t db, int scale_d) {
    asm volatile("{\n.reg .pred p;\nsetp.ne.b32 p, %37, 0;\n"
        "wgmma.mma_async.sync.aligned.m64n64k16.f32.bf16.bf16 "
        "{%0, %1, %2, %3, %4, %5, %6, %7, %8, %9, %10, %11, %12, %13, %14, %15, "
        "%16, %17, %18, %19, %20, %21, %22, %23, %24, %25, %26, %27, %28, %29, %30, %31}, "
        "{%32, %33, %34, %35}, %36, p, 1, 1, 0;\n}\n"
        : "+f"(d[0]), "+f"(d[1]), "+f"(d[2]), "+f"(d[3]), "+f"(d[4]), "+f"(d[5]), "+f"(d[6]), "+f"(d[7]),
          "+f"(d[8]), "+f"(d[9]), "+f"(d[10]), "+f"(d[11]), "+f"(d[12]), "+f"(d[13]), "+f"(d[14]), "+f"(d[15]),
          "+f"(d[16]), "+f"(d[17]), "+f"(d[18]), "+f"(d[19]), "+f"(d[20]), "+f"(d[21]), "+f"(d[22]), "+f"(d[23]),
          "+f"(d[24]), "+f"(d[25]), "+f"(d[26]), "+f"(d[27]), "+f"(d[28]), "+f"(d[29]), "+f"(d[30]), "+f"(d[31])
        : "r"(a0), "r"(a1), "r"(a2), "r"(a3), "l"(db), "r"(scale_d));
}
template <int N>
__device__ __forceinline__ void wgmma_n64_rs_tb(float (&d)[N], uint32_t a0, uint32_t a1, uint32_t a2, uint32_t a3, uint64_t db, int scale_d) {
    asm volatile("{\n.reg .pred p;\nsetp.ne.b32 p, %37, 0;\n"
        "wgmma.mma_async.sync.aligned.m64n64k16.f32.bf16.bf16 "
        "{%0, %1, %2, %3, %4, %5, %6, %7, %8, %9, %10, %11, %12, %13, %14, %15, "
        "%16, %17, %18, %19, %20, %21, %22, %23, %24, %25, %26, %27, %28, %29, %30, %31}, "
        "{%32, %33, %34, %35}, %36, p, 1, 1, 1;\n}\n"
        : "+f"(d[0]), "+f"(d[1]), "+f"(d[2]), "+f"(d[3]), "+f"(d[4]), "+f"(d[5]), "+f"(d[6]), "+f"(d[7]),
          "+f"(d[8]), "+f"(d[9]), "+f"(d[10]), "+f"(d[11]), "+f"(d[12]), "+f"(d[13]), "+f"(d[14]), "+f"(d[15]),
          "+f"(d[16]), "+f"(d[17]), "+f"(d[18]), "+f"(d[19]), "+f"(d[20]), "+f"(d[21]), "+f"(d[22]), "+f"(d[23]),
          "+f"(d[24]), "+f"(d[25]), "+f"(d[26]), "+f"(d[27]), "+f"(d[28]), "+f"(d[29]), "+f"(d[30]), "+f"(d[31])
        : "r"(a0), "r"(a1), "r"(a2), "r"(a3), "l"(db), "r"(scale_d));
}
template <int N>
__device__ __forceinline__ void wgmma_n72_rs_tb(float (&d)[N], uint32_t a0, uint32_t a1, uint32_t a2, uint32_t a3, uint64_t db, int scale_d) {
    asm volatile("{\n.reg .pred p;\nsetp.ne.b32 p, %41, 0;\n"
        "wgmma.mma_async.sync.aligned.m64n72k16.f32.bf16.bf16 "
        "{%0, %1, %2, %3, %4, %5, %6, %7, %8, %9, %10, %11, %12, %13, %14, %15, "
        "%16, %17, %18, %19, %20, %21, %22, %23, %24, %25, %26, %27, %28, %29, %30, %31, "
        "%32, %33, %34, %35}, "
        "{%36, %37, %38, %39}, %40, p, 1, 1, 1;\n}\n"
        : "+f"(d[0]), "+f"(d[1]), "+f"(d[2]), "+f"(d[3]), "+f"(d[4]), "+f"(d[5]), "+f"(d[6]), "+f"(d[7]),
          "+f"(d[8]), "+f"(d[9]), "+f"(d[10]), "+f"(d[11]), "+f"(d[12]), "+f"(d[13]), "+f"(d[14]), "+f"(d[15]),
          "+f"(d[16]), "+f"(d[17]), "+f"(d[18]), "+f"(d[19]), "+f"(d[20]), "+f"(d[21]), "+f"(d[22]), "+f"(d[23]),
          "+f"(d[24]), "+f"(d[25]), "+f"(d[26]), "+f"(d[27]), "+f"(d[28]), "+f"(d[29]), "+f"(d[30]), "+f"(d[31]),
          "+f"(d[32]), "+f"(d[33]), "+f"(d[34]), "+f"(d[35])
        : "r"(a0), "r"(a1), "r"(a2), "r"(a3), "l"(db), "r"(scale_d));
}
template <int N>
__device__ __forceinline__ void wgmma_n128_rs(float (&d)[N], uint32_t a0, uint32_t a1, uint32_t a2, uint32_t a3, uint64_t db, int scale_d) {
    asm volatile("{\n.reg .pred p;\nsetp.ne.b32 p, %69, 0;\n"
        "wgmma.mma_async.sync.aligned.m64n128k16.f32.bf16.bf16 "
        "{%0, %1, %2, %3, %4, %5, %6, %7, %8, %9, %10, %11, %12, %13, %14, %15, "
        "%16, %17, %18, %19, %20, %21, %22, %23, %24, %25, %26, %27, %28, %29, %30, %31, "
        "%32, %33, %34, %35, %36, %37, %38, %39, %40, %41, %42, %43, %44, %45, %46, %47, "
        "%48, %49, %50, %51, %52, %53, %54, %55, %56, %57, %58, %59, %60, %61, %62, %63}, "
        "{%64, %65, %66, %67}, %68, p, 1, 1, 0;\n}\n"
        : "+f"(d[0]), "+f"(d[1]), "+f"(d[2]), "+f"(d[3]), "+f"(d[4]), "+f"(d[5]), "+f"(d[6]), "+f"(d[7]),
          "+f"(d[8]), "+f"(d[9]), "+f"(d[10]), "+f"(d[11]), "+f"(d[12]), "+f"(d[13]), "+f"(d[14]), "+f"(d[15]),
          "+f"(d[16]), "+f"(d[17]), "+f"(d[18]), "+f"(d[19]), "+f"(d[20]), "+f"(d[21]), "+f"(d[22]), "+f"(d[23]),
          "+f"(d[24]), "+f"(d[25]), "+f"(d[26]), "+f"(d[27]), "+f"(d[28]), "+f"(d[29]), "+f"(d[30]), "+f"(d[31]),
          "+f"(d[32]), "+f"(d[33]), "+f"(d[34]), "+f"(d[35]), "+f"(d[36]), "+f"(d[37]), "+f"(d[38]), "+f"(d[39]),
          "+f"(d[40]), "+f"(d[41]), "+f"(d[42]), "+f"(d[43]), "+f"(d[44]), "+f"(d[45]), "+f"(d[46]), "+f"(d[47]),
          "+f"(d[48]), "+f"(d[49]), "+f"(d[50]), "+f"(d[51]), "+f"(d[52]), "+f"(d[53]), "+f"(d[54]), "+f"(d[55]),
          "+f"(d[56]), "+f"(d[57]), "+f"(d[58]), "+f"(d[59]), "+f"(d[60]), "+f"(d[61]), "+f"(d[62]), "+f"(d[63])
        : "r"(a0), "r"(a1), "r"(a2), "r"(a3), "l"(db), "r"(scale_d));
}
template <int N>
__device__ __forceinline__ void wgmma_n128_ss(float (&d)[N], uint64_t da, uint64_t db, int scale_d) {
    asm volatile("{\n.reg .pred p;\nsetp.ne.b32 p, %66, 0;\n"
        "wgmma.mma_async.sync.aligned.m64n128k16.f32.bf16.bf16 "
        "{%0, %1, %2, %3, %4, %5, %6, %7, %8, %9, %10, %11, %12, %13, %14, %15, "
        "%16, %17, %18, %19, %20, %21, %22, %23, %24, %25, %26, %27, %28, %29, %30, %31, "
        "%32, %33, %34, %35, %36, %37, %38, %39, %40, %41, %42, %43, %44, %45, %46, %47, "
        "%48, %49, %50, %51, %52, %53, %54, %55, %56, %57, %58, %59, %60, %61, %62, %63}, "
        "%64, %65, p, 1, 1, 0, 0;\n}\n"
        : "+f"(d[0]), "+f"(d[1]), "+f"(d[2]), "+f"(d[3]), "+f"(d[4]), "+f"(d[5]), "+f"(d[6]), "+f"(d[7]),
          "+f"(d[8]), "+f"(d[9]), "+f"(d[10]), "+f"(d[11]), "+f"(d[12]), "+f"(d[13]), "+f"(d[14]), "+f"(d[15]),
          "+f"(d[16]), "+f"(d[17]), "+f"(d[18]), "+f"(d[19]), "+f"(d[20]), "+f"(d[21]), "+f"(d[22]), "+f"(d[23]),
          "+f"(d[24]), "+f"(d[25]), "+f"(d[26]), "+f"(d[27]), "+f"(d[28]), "+f"(d[29]), "+f"(d[30]), "+f"(d[31]),
          "+f"(d[32]), "+f"(d[33]), "+f"(d[34]), "+f"(d[35]), "+f"(d[36]), "+f"(d[37]), "+f"(d[38]), "+f"(d[39]),
          "+f"(d[40]), "+f"(d[41]), "+f"(d[42]), "+f"(d[43]), "+f"(d[44]), "+f"(d[45]), "+f"(d[46]), "+f"(d[47]),
          "+f"(d[48]), "+f"(d[49]), "+f"(d[50]), "+f"(d[51]), "+f"(d[52]), "+f"(d[53]), "+f"(d[54]), "+f"(d[55]),
          "+f"(d[56]), "+f"(d[57]), "+f"(d[58]), "+f"(d[59]), "+f"(d[60]), "+f"(d[61]), "+f"(d[62]), "+f"(d[63])
        : "l"(da), "l"(db), "r"(scale_d));
}
template <int N>
__device__ __forceinline__ void wgmma_n256_rs_tb(float (&d)[N], uint32_t a0, uint32_t a1, uint32_t a2, uint32_t a3, uint64_t db, int scale_d) {
    asm volatile("{\n.reg .pred p;\nsetp.ne.b32 p, %133, 0;\n"
        "wgmma.mma_async.sync.aligned.m64n256k16.f32.bf16.bf16 "
        "{%0, %1, %2, %3, %4, %5, %6, %7, %8, %9, %10, %11, %12, %13, %14, %15, "
        "%16, %17, %18, %19, %20, %21, %22, %23, %24, %25, %26, %27, %28, %29, %30, %31, "
        "%32, %33, %34, %35, %36, %37, %38, %39, %40, %41, %42, %43, %44, %45, %46, %47, "
        "%48, %49, %50, %51, %52, %53, %54, %55, %56, %57, %58, %59, %60, %61, %62, %63, "
        "%64, %65, %66, %67, %68, %69, %70, %71, %72, %73, %74, %75, %76, %77, %78, %79, "
        "%80, %81, %82, %83, %84, %85, %86, %87, %88, %89, %90, %91, %92, %93, %94, %95, "
        "%96, %97, %98, %99, %100, %101, %102, %103, %104, %105, %106, %107, %108, %109, %110, %111, "
        "%112, %113, %114, %115, %116, %117, %118, %119, %120, %121, %122, %123, %124, %125, %126, %127}, "
        "{%128, %129, %130, %131}, %132, p, 1, 1, 1;\n}\n"
        : "+f"(d[0]), "+f"(d[1]), "+f"(d[2]), "+f"(d[3]), "+f"(d[4]), "+f"(d[5]), "+f"(d[6]), "+f"(d[7]),
          "+f"(d[8]), "+f"(d[9]), "+f"(d[10]), "+f"(d[11]), "+f"(d[12]), "+f"(d[13]), "+f"(d[14]), "+f"(d[15]),
          "+f"(d[16]), "+f"(d[17]), "+f"(d[18]), "+f"(d[19]), "+f"(d[20]), "+f"(d[21]), "+f"(d[22]), "+f"(d[23]),
          "+f"(d[24]), "+f"(d[25]), "+f"(d[26]), "+f"(d[27]), "+f"(d[28]), "+f"(d[29]), "+f"(d[30]), "+f"(d[31]),
          "+f"(d[32]), "+f"(d[33]), "+f"(d[34]), "+f"(d[35]), "+f"(d[36]), "+f"(d[37]), "+f"(d[38]), "+f"(d[39]),
          "+f"(d[40]), "+f"(d[41]), "+f"(d[42]), "+f"(d[43]), "+f"(d[44]), "+f"(d[45]), "+f"(d[46]), "+f"(d[47]),
          "+f"(d[48]), "+f"(d[49]), "+f"(d[50]), "+f"(d[51]), "+f"(d[52]), "+f"(d[53]), "+f"(d[54]), "+f"(d[55]),
          "+f"(d[56]), "+f"(d[57]), "+f"(d[58]), "+f"(d[59]), "+f"(d[60]), "+f"(d[61]), "+f"(d[62]), "+f"(d[63]),
          "+f"(d[64]), "+f"(d[65]), "+f"(d[66]), "+f"(d[67]), "+f"(d[68]), "+f"(d[69]), "+f"(d[70]), "+f"(d[71]),
          "+f"(d[72]), "+f"(d[73]), "+f"(d[74]), "+f"(d[75]), "+f"(d[76]), "+f"(d[77]), "+f"(d[78]), "+f"(d[79]),
          "+f"(d[80]), "+f"(d[81]), "+f"(d[82]), "+f"(d[83]), "+f"(d[84]), "+f"(d[85]), "+f"(d[86]), "+f"(d[87]),
          "+f"(d[88]), "+f"(d[89]), "+f"(d[90]), "+f"(d[91]), "+f"(d[92]), "+f"(d[93]), "+f"(d[94]), "+f"(d[95]),
          "+f"(d[96]), "+f"(d[97]), "+f"(d[98]), "+f"(d[99]), "+f"(d[100]), "+f"(d[101]), "+f"(d[102]), "+f"(d[103]),
          "+f"(d[104]), "+f"(d[105]), "+f"(d[106]), "+f"(d[107]), "+f"(d[108]), "+f"(d[109]), "+f"(d[110]), "+f"(d[111]),
          "+f"(d[112]), "+f"(d[113]), "+f"(d[114]), "+f"(d[115]), "+f"(d[116]), "+f"(d[117]), "+f"(d[118]), "+f"(d[119]),
          "+f"(d[120]), "+f"(d[121]), "+f"(d[122]), "+f"(d[123]), "+f"(d[124]), "+f"(d[125]), "+f"(d[126]), "+f"(d[127])
        : "r"(a0), "r"(a1), "r"(a2), "r"(a3), "l"(db), "r"(scale_d));
}

constexpr float kC1 = 0.25f * 1.4426950408889634f;
constexpr float kC2 = -1.4426950408889634f / 32.0f;
constexpr float kC3 = -4.0f;

template <int V> struct Int { static constexpr int value = V; };
__device__ __forceinline__ uint32_t slot_addr(uint32_t sb, int s) { return sb + SM_SLOT + s * SLOT_BYTES; }
__device__ __forceinline__ uint32_t bar_addr(uint32_t sb, int b) { return sb + SM_BAR + b * 8; }

__device__ __forceinline__ void release_pair(uint32_t bar, uint32_t rank, uint32_t count = 1) {
    mbar_arrive_n(bar, rank, count);
    mbar_arrive_n(bar, rank ^ 1, count);
}

__device__ __forceinline__ float row_bias(uint32_t tile, int row, int half) {
    const uint32_t base = tile + half * 16384 + row * 128;
    const uint32_t sw = ((row & 7) ^ (half << 2)) << 4;
    float s0 = 0.f, s1 = 0.f, s2 = 0.f, s3 = 0.f;
#pragma unroll
    for (int bt = 0; bt < 4; bt++) {
        uint32_t x[4][4];
#pragma unroll
        for (int i = 0; i < 4; i++)
            asm volatile("ld.shared.v4.u32 {%0, %1, %2, %3}, [%4];" : "=r"(x[i][0]), "=r"(x[i][1]), "=r"(x[i][2]), "=r"(x[i][3])
                         : "r"(base + (bt >> 1) * 8192 + ((((bt & 1) * 4 + i) << 4) ^ sw)));
#pragma unroll
        for (int i = 0; i < 4; i++) {
            float a;
            a = __uint_as_float(x[i][0] << 16); s0 = fmaf(a, a, s0);
            a = __uint_as_float(x[i][0] & 0xffff0000u); s1 = fmaf(a, a, s1);
            a = __uint_as_float(x[i][1] << 16); s2 = fmaf(a, a, s2);
            a = __uint_as_float(x[i][1] & 0xffff0000u); s3 = fmaf(a, a, s3);
            a = __uint_as_float(x[i][2] << 16); s0 = fmaf(a, a, s0);
            a = __uint_as_float(x[i][2] & 0xffff0000u); s1 = fmaf(a, a, s1);
            a = __uint_as_float(x[i][3] << 16); s2 = fmaf(a, a, s2);
            a = __uint_as_float(x[i][3] & 0xffff0000u); s3 = fmaf(a, a, s3);
        }
    }
    float s = (s0 + s1) + (s2 + s3);
    s += __shfl_xor_sync(0xffffffffu, s, 1);
    return fmaf(s, kC2, kC3);
}
__device__ __forceinline__ void st_async_f32(uint32_t addr, float v, uint32_t bar, uint32_t cta) {
    asm volatile("{\n.reg .b32 ra, rb;\nmapa.shared::cluster.u32 ra, %0, %3;\nmapa.shared::cluster.u32 rb, %2, %3;\n"
                 "st.async.weak.shared::cluster.mbarrier::complete_tx::bytes.f32 [ra], %1, [rb];\n}"
                 :: "r"(addr), "f"(v), "r"(bar), "r"(cta) : "memory");
}

__device__ __forceinline__ void load_q_frags(uint32_t (&f)[64], float& qb0, float& qb1, uint32_t tile, int wq, int lane) {
    const int row = wq * 16 + (lane & 7) + ((lane >> 3) & 1) * 8;
    const uint32_t base = tile + row * 128;
#pragma unroll
    for (int k = 0; k < 16; k++) {
        const int chunk = 2 * k + (lane >> 4);
        asm volatile("ldmatrix.sync.aligned.m8n8.x4.shared.b16 {%0, %1, %2, %3}, [%4];"
                     : "=r"(f[4 * k]), "=r"(f[4 * k + 1]), "=r"(f[4 * k + 2]), "=r"(f[4 * k + 3])
                     : "r"(base + (k >> 2) * 8192 + (((chunk & 7) ^ (row & 7)) << 4)));
    }
    float s0 = 0.f, s1 = 0.f, s2 = 0.f, s3 = 0.f;
#pragma unroll
    for (int k = 0; k < 32; k++) {
        float a;
        a = __uint_as_float(f[2 * k] << 16); s0 = fmaf(a, a, s0);
        a = __uint_as_float(f[2 * k] & 0xffff0000u); s1 = fmaf(a, a, s1);
        a = __uint_as_float(f[2 * k + 1] << 16); s2 = fmaf(a, a, s2);
        a = __uint_as_float(f[2 * k + 1] & 0xffff0000u); s3 = fmaf(a, a, s3);
    }
    s0 += s1; s2 += s3;
    s0 += __shfl_xor_sync(0xffffffffu, s0, 1); s2 += __shfl_xor_sync(0xffffffffu, s2, 1);
    s0 += __shfl_xor_sync(0xffffffffu, s0, 2); s2 += __shfl_xor_sync(0xffffffffu, s2, 2);
    qb0 = fmaf(s0, kC2, kC3);
    qb1 = fmaf(s2, kC2, kC3);
}
__device__ __forceinline__ void gemm3(float (&d)[64], const uint32_t (&f)[64], uint32_t b01, uint32_t b23) {
    const uint64_t d0 = desc_sw128(b01, 16), d1 = desc_sw128(b23, 16);
    wg_fence();
#pragma unroll
    for (int k = 0; k < 16; k++)
        wgmma_n128_rs(d, f[4 * k], f[4 * k + 1], f[4 * k + 2], f[4 * k + 3],
                      (k < 8 ? d0 : d1) + ((((k >> 2) & 1) * 16384 + (k & 3) * 32) >> 4), k > 0);
    wg_commit();
}
template <int K0>
__device__ __forceinline__ void gemm3_ss(float (&d)[64], uint32_t qs, uint32_t pb) {
    const uint64_t da = desc_sw128(qs + (K0 >> 2) * 8192, 16), db = desc_sw128(pb, 16);
#pragma unroll
    for (int k = 0; k < 8; k++)
        wgmma_n128_ss(d, da + (((k >> 2) * 8192 + (k & 3) * 32) >> 4), db + (((k >> 2) * 16384 + (k & 3) * 32) >> 4), (K0 + k) > 0);
}
template <int K0>
__device__ __forceinline__ void tile_sumsq(float& s0, float& s1, uint32_t tile, int wq, int lane) {
    const int row = wq * 16 + (lane & 7) + ((lane >> 3) & 1) * 8;
    const uint32_t base = tile + row * 128;
    float t0 = 0.f, t1 = 0.f;
#pragma unroll
    for (int kb = 0; kb < 2; kb++) {
        uint32_t x[4][4];
#pragma unroll
        for (int i = 0; i < 4; i++) {
            const int k = K0 + kb * 4 + i, chunk = 2 * k + (lane >> 4);
            asm volatile("ldmatrix.sync.aligned.m8n8.x4.shared.b16 {%0, %1, %2, %3}, [%4];"
                         : "=r"(x[i][0]), "=r"(x[i][1]), "=r"(x[i][2]), "=r"(x[i][3])
                         : "r"(base + (k >> 2) * 8192 + (((chunk & 7) ^ (row & 7)) << 4)));
        }
#pragma unroll
        for (int i = 0; i < 4; i++) {
            float a;
            a = __uint_as_float(x[i][0] << 16); s0 = fmaf(a, a, s0);
            a = __uint_as_float(x[i][0] & 0xffff0000u); t0 = fmaf(a, a, t0);
            a = __uint_as_float(x[i][1] << 16); s1 = fmaf(a, a, s1);
            a = __uint_as_float(x[i][1] & 0xffff0000u); t1 = fmaf(a, a, t1);
            a = __uint_as_float(x[i][2] << 16); s0 = fmaf(a, a, s0);
            a = __uint_as_float(x[i][2] & 0xffff0000u); t0 = fmaf(a, a, t0);
            a = __uint_as_float(x[i][3] << 16); s1 = fmaf(a, a, s1);
            a = __uint_as_float(x[i][3] & 0xffff0000u); t1 = fmaf(a, a, t1);
        }
    }
    s0 += t0;
    s1 += t1;
}
__device__ __forceinline__ void pin_after(float& a, float& b, uint32_t token, uint32_t zero) {
    a = __uint_as_float(__float_as_uint(a) ^ (token & zero));
    b = __uint_as_float(__float_as_uint(b) ^ (token & zero));
}
template <int O>
__device__ __forceinline__ void exp_to_regs(uint32_t (&phi)[64], const float (&a)[64], float qb0, float qb1) {
#pragma unroll
    for (int j = 0; j < 16; j++) {
        phi[O + 2 * j] = pack_bf16(ex2(fmaf(a[4 * j], kC1, qb0)), ex2(fmaf(a[4 * j + 1], kC1, qb0)));
        phi[O + 2 * j + 1] = pack_bf16(ex2(fmaf(a[4 * j + 2], kC1, qb1)), ex2(fmaf(a[4 * j + 3], kC1, qb1)));
    }
}
template <int N>
__device__ __forceinline__ void fence_regs(float (&d)[N]) {
#pragma unroll
    for (int i = 0; i < N; i++) asm volatile("" : "+f"(d[i]) :: "memory");
}
template <int ID> __device__ __forceinline__ void bar_sync() { asm volatile("bar.sync %0, 256;" :: "n"(ID) : "memory"); }
template <int ID> __device__ __forceinline__ void bar_arrive() { asm volatile("bar.arrive %0, 256;" :: "n"(ID) : "memory"); }

template <int N>
__device__ __forceinline__ void store_out(const float (&o)[N], float inv0, float inv1, __nv_bfloat16* p0) {
#pragma unroll
    for (int t = 0; t < 2; t++) {
#pragma unroll
        for (int i = 0; i < 2; i++) {
            const float inv = i ? inv1 : inv0;
            uint4 v;
            v.x = pack_bf16(o[16 * t + 2 * i] * inv, o[16 * t + 2 * i + 1] * inv);
            v.y = pack_bf16(o[16 * t + 4 + 2 * i] * inv, o[16 * t + 4 + 2 * i + 1] * inv);
            v.z = pack_bf16(o[16 * t + 8 + 2 * i] * inv, o[16 * t + 8 + 2 * i + 1] * inv);
            v.w = pack_bf16(o[16 * t + 12 + 2 * i] * inv, o[16 * t + 12 + 2 * i + 1] * inv);
            *reinterpret_cast<uint4*>(p0 + i * 8 * kDim + t * 32) = v;
        }
    }
}

__global__ void __cluster_dims__(2, 1, 1) __launch_bounds__(384, 1)
performer_kernel(const __grid_constant__ CUtensorMap tm_q, const __grid_constant__ CUtensorMap tm_k,
                 const __grid_constant__ CUtensorMap tm_v, const __grid_constant__ CUtensorMap tm_p,
                 const uint8_t* __restrict__ kptr, const uint8_t* __restrict__ pptr, __nv_bfloat16* __restrict__ out) {
    extern __shared__ __align__(1024) uint8_t smem[];
    const uint32_t sb = (uint32_t)__cvta_generic_to_shared(smem);
    const int tid = threadIdx.x, lane = tid & 31;
    const int warp = __shfl_sync(0xffffffffu, tid >> 5, 0);
    uint32_t rank;
    asm volatile("mov.u32 %0, %%cluster_ctarank;" : "=r"(rank));
    const int cta = blockIdx.x, pair = cta >> 1, h = pair >> 2, sc = pair & 3;

    if (tid == 64) {
        asm volatile("cp.async.bulk.prefetch.L2.global [%0], %1;"
                     :: "l"(kptr + (size_t)(h * kSeq + sc * 512 + rank * 32) * 512), "r"(16384) : "memory");
        asm volatile("cp.async.bulk.prefetch.L2.global [%0], %1;" :: "l"(pptr + cta * 1024), "r"(1024) : "memory");
    }
    if (tid == 32) {
        asm volatile("prefetch.tensormap [%0];" :: "l"(&tm_k) : "memory");
        asm volatile("prefetch.tensormap [%0];" :: "l"(&tm_p) : "memory");
        asm volatile("prefetch.tensormap [%0];" :: "l"(&tm_v) : "memory");
        asm volatile("prefetch.tensormap [%0];" :: "l"(&tm_q) : "memory");
    }
    if (tid == 0) {
        mbar_init(bar_addr(sb, B_PROJ), 1);
#pragma unroll
        for (int i = 0; i < 5; i++) { mbar_init(bar_addr(sb, B_FULL + i), 1); mbar_init(bar_addr(sb, B_EMPTY + i), 20); }
#pragma unroll
        for (int i = 0; i < 4; i++) { mbar_init(bar_addr(sb, B_KV + i), 1); mbar_init(bar_addr(sb, B_NORM + i), 1); }
#pragma unroll
        for (int i = 0; i < 2; i++) { mbar_init(bar_addr(sb, B_SFREE + i), 1); mbar_init(bar_addr(sb, B_ACONS + i), 4); }
#pragma unroll
        for (int i = 0; i < 2; i++) mbar_init(bar_addr(sb, B_STG + i), 8);
        mbar_init(bar_addr(sb, B_DUMPED), 1);
        mbar_init(bar_addr(sb, B_PO01), 1);
        mbar_init(bar_addr(sb, B_PO23), 1);
        mbar_init(bar_addr(sb, B_ZERO), 1);
        mbar_init(bar_addr(sb, B_PDEAD), 8);
        mbar_init(bar_addr(sb, B_P0DEAD), 8);
        mbar_init(bar_addr(sb, B_B0DEAD), 4);
        mbar_init(bar_addr(sb, B_KSUM), 1);
        mbar_init(bar_addr(sb, B_GO), 1);
        mbar_init(bar_addr(sb, B_QARR), 1);
        asm volatile("fence.mbarrier_init.release.cluster;" ::: "memory");
    }
    __syncwarp();
    asm volatile("barrier.cluster.arrive.relaxed.aligned;" ::: "memory");
    asm volatile("barrier.cluster.wait.aligned;" ::: "memory");
    if (tid == 0) {
        const int row0 = h * kSeq + sc * 512;
        const uint64_t pol = policy_evict_first();
        mbar_expect_tx(bar_addr(sb, B_FULL + 0), SLOT_BYTES);
        tma_load_mc(slot_addr(sb, 0) + rank * 16384, &tm_k, bar_addr(sb, B_FULL + 0), row0, rank * 2, pol);
        mbar_expect_tx(bar_addr(sb, B_PROJ), 65536);
        tma_load(sb + SM_P0, &tm_p, bar_addr(sb, B_PROJ), rank * 128, 0);
        tma_load(sb + SM_P0 + 32768, &tm_p, bar_addr(sb, B_PROJ), rank * 128, 2);
        mbar_expect_tx(bar_addr(sb, B_FULL + 1), SLOT_BYTES);
        tma_load_mc(slot_addr(sb, 1) + rank * 16384, &tm_v, bar_addr(sb, B_FULL + 1), row0, rank * 2, pol);
        mbar_expect_tx(bar_addr(sb, B_FULL + 2), SLOT_BYTES);
        tma_load_mc(slot_addr(sb, 2) + rank * 16384, &tm_k, bar_addr(sb, B_FULL + 2), row0 + 64, rank * 2, pol);
    }
    __syncwarp();

    if (warp < 4) {
        reg_dealloc<40>();
        if (warp == 0) {
            if (lane == 0) {
                const int row0 = h * kSeq + sc * 512;
                const uint64_t pol = policy_evict_first();
                auto load_item = [&](int i) {
                    const int s = i % 5;
                    if (i >= 5) mbar_wait(bar_addr(sb, B_EMPTY + s), (i / 5 - 1) & 1);
                    mbar_expect_tx(bar_addr(sb, B_FULL + s), SLOT_BYTES);
                    tma_load_mc(slot_addr(sb, s) + rank * 16384, (i & 1) ? &tm_v : &tm_k, bar_addr(sb, B_FULL + s),
                                row0 + (i >> 1) * 64, rank * 2, pol);
                };
                mbar_wait(bar_addr(sb, B_FULL + 0), 0);
                load_item(3);
                mbar_wait(bar_addr(sb, B_FULL + 1), 0);
                load_item(4);
#pragma unroll 1
                for (int i = 5; i < 16; i++) {
                    load_item(i);
                    if (i == 6) mbar_arrive(bar_addr(sb, B_GO));
                }
                const int qrow = row0 + rank * 256;
                auto load_q = [&](int piece, int slot) {
                    mbar_expect_tx(bar_addr(sb, B_FULL + slot), SLOT_BYTES);
                    tma_load_ef(slot_addr(sb, slot), &tm_q, bar_addr(sb, B_FULL + slot), qrow + piece * 64, 0, pol);
                    tma_load_ef(slot_addr(sb, slot) + 16384, &tm_q, bar_addr(sb, B_FULL + slot), qrow + piece * 64, 2, pol);
                };
                mbar_wait(bar_addr(sb, B_EMPTY + 1), 0);
                load_q(0, S_QA);
                mbar_wait(bar_addr(sb, B_EMPTY + 4), 0);
                load_q(1, S_QB);
                mbar_wait(bar_addr(sb, B_EMPTY + 3), 0);
                mbar_expect_tx(bar_addr(sb, B_PO01), SLOT_BYTES);
                tma_load(slot_addr(sb, S_PO01), &tm_p, bar_addr(sb, B_PO01), (rank ^ 1) * 128, 0);
                mbar_wait(bar_addr(sb, B_EMPTY + 2), 0);
                mbar_expect_tx(bar_addr(sb, B_PO23), SLOT_BYTES);
                tma_load(slot_addr(sb, S_PO23), &tm_p, bar_addr(sb, B_PO23), (rank ^ 1) * 128, 2);
                mbar_wait(bar_addr(sb, B_ACONS + 0), 0);
                load_q(2, S_QA);
                mbar_wait(bar_addr(sb, B_ACONS + 1), 0);
                load_q(3, S_QB);
                mbar_wait(bar_addr(sb, B_FULL + S_QB), 0);
                mbar_arrive(bar_addr(sb, B_QARR));
            }
            __syncwarp();
        } else if (warp < 3) {
            const int w = warp - 1;
            const int row = rank * 32 + w * 16 + (lane >> 1);
            int s = 0, ph = 0;
#pragma unroll 1
            for (int t = 0; t < 8; t++) {
                const uint32_t nbar = bar_addr(sb, B_NORM + (t & 3));
                if (w == 0 && lane == 0) mbar_expect_tx(nbar, 256);
                mbar_wait(bar_addr(sb, B_FULL + s), ph);
                const float b = row_bias(slot_addr(sb, s), row, lane & 1);
                if (!(lane & 1)) {
                    const uint32_t dst = sb + SM_NORM + (t & 3) * 256 + row * 4;
                    st_async_f32(dst, b, nbar, 0);
                    st_async_f32(dst, b, nbar, 1);
                }
                __syncwarp();
                if (lane == 0) release_pair(bar_addr(sb, B_EMPTY + s), rank);
                s += 2;
                if (s >= 5) { s -= 5; ph ^= 1; }
            }
            if (w == 0 && lane == 0) {
                const uint32_t src = slot_addr(sb, S_STG);
                mbar_wait(bar_addr(sb, B_ZERO), 0);
#pragma unroll 1
                for (int r = 0; r < 2; r++) {
                    mbar_wait(bar_addr(sb, B_STG + r), 0);
                    if (r == 1) mbar_wait(bar_addr(sb, B_QARR), 0);
                    asm volatile("fence.proxy.async.global;" ::: "memory");
                    if (r == 0)
                        asm volatile("cp.reduce.async.bulk.global.shared::cta.bulk_group.add.f32 [%0], [%1], %2;"
                                     :: "l"(g_ksum + h * 256 + rank * 128), "r"(sb + SM_KS), "r"(512) : "memory");
#pragma unroll 1
                    for (int b = 0; b < 8; b++) {
                        const int g2 = b >> 2, u = (b >> 1) & 1, hf = b & 1;
                        uint8_t* dst = reinterpret_cast<uint8_t*>(g_kvacc + h * 8192) + (2 * r + u) * 32768 + (rank * 128 + g2 * 64 + hf * 32) * 128;
                        asm volatile("cp.reduce.async.bulk.global.shared::cta.bulk_group.add.noftz.bf16 [%0], [%1], %2;"
                                     :: "l"(dst), "r"(src + b * 4096), "r"(4096) : "memory");
                        asm volatile("cp.async.bulk.commit_group;" ::: "memory");
                        asm volatile("cp.async.bulk.wait_group.read 0;" ::: "memory");
                    }
                    mbar_arrive(bar_addr(sb, B_SFREE + r));
                    asm volatile("cp.async.bulk.wait_group 0;" ::: "memory");
                    asm volatile("fence.proxy.async.global;" ::: "memory");
                    red_add_u32(&g_flag_dump[h * 64 + r * 32], 1);
                    if (r == 0) mbar_arrive(bar_addr(sb, B_DUMPED));
                }
            }
            __syncwarp();
        } else {
            unsigned target = 0;
            if (lane == 0) target = ld_relaxed_gpu(&g_flag_dump[h * 64 + 32]) + 8;
            mbar_wait(bar_addr(sb, B_GO), 0);
            uint4* z = g_kvacc + h * 8192 + (cta & 7) * 1024;
#pragma unroll 4
            for (int i = 0; i < 32; i++) z[i * 32 + lane] = make_uint4(0, 0, 0, 0);
            g_ksum[h * 256 + (cta & 7) * 32 + lane] = 0.f;
            __syncwarp();
            if (lane == 0) {
                fence_gpu();
                red_add_u32(&g_flag_zero[h * 32], 1);
                spin_flag(&g_flag_zero[h * 32], target);
                asm volatile("fence.proxy.async.global;" ::: "memory");
                mbar_arrive(bar_addr(sb, B_ZERO));
                mbar_wait(bar_addr(sb, B_DUMPED), 0);
                spin_flag(&g_flag_dump[h * 64], target);
                asm volatile("fence.proxy.async.global;" ::: "memory");
            }
            __syncwarp();
            float kv8[8];
#pragma unroll
            for (int i = 0; i < 8; i++) kv8[i] = __ldcg(g_ksum + h * 256 + i * 32 + lane);
            const uint8_t* kvsrc = reinterpret_cast<const uint8_t*>(g_kvacc + h * 8192);
            if (lane == 0) {
                mbar_wait(bar_addr(sb, B_P0DEAD), 0);
                mbar_expect_tx(bar_addr(sb, B_KV + 0), SLOT_BYTES);
                bulk_load(sb + SM_P0, kvsrc, SLOT_BYTES, bar_addr(sb, B_KV + 0));
                mbar_expect_tx(bar_addr(sb, B_KV + 1), SLOT_BYTES);
                bulk_load(sb + SM_P0 + 32768, kvsrc + 32768, SLOT_BYTES, bar_addr(sb, B_KV + 1));
            }
            __syncwarp();
            mbar_wait(bar_addr(sb, B_B0DEAD), 0);
#pragma unroll
            for (int i = 0; i < 8; i++) {
                const int m = i * 32 + lane;
                asm volatile("st.shared.v4.u32 [%0], {%1, %1, %1, %1};" :: "r"(slot_addr(sb, S_QA) + m * 128 + ((m & 7) << 4)), "r"(pack_bf16(kv8[i], kv8[i])) : "memory");
            }
            asm volatile("fence.proxy.async.shared::cta;" ::: "memory");
            __syncwarp();
            if (lane == 0) {
                mbar_arrive(bar_addr(sb, B_KSUM));
                spin_flag(&g_flag_dump[h * 64 + 32], target);
                asm volatile("fence.proxy.async.global;" ::: "memory");
                mbar_wait(bar_addr(sb, B_SFREE + 1), 0);
                mbar_expect_tx(bar_addr(sb, B_KV + 2), SLOT_BYTES);
                bulk_load(slot_addr(sb, S_STG), kvsrc + 65536, SLOT_BYTES, bar_addr(sb, B_KV + 2));
                mbar_wait(bar_addr(sb, B_PDEAD), 0);
                mbar_expect_tx(bar_addr(sb, B_KV + 3), SLOT_BYTES);
                bulk_load(slot_addr(sb, S_PO01), kvsrc + 98304, SLOT_BYTES, bar_addr(sb, B_KV + 3));
            }
            __syncwarp();
        }
        asm volatile("barrier.cluster.arrive.relaxed.aligned;" ::: "memory");
        asm volatile("barrier.cluster.wait.aligned;" ::: "memory");
    } else {
        reg_alloc<232>();
        const int w = (warp - 4) >> 2, wq = warp & 3, g = lane >> 2, c = lane & 3;
        float ks0 = 0.f, ks1 = 0.f, qb0, qb1;
        uint32_t f[64], pk[64];
        auto stage = [&](auto round) {
            constexpr int R = decltype(round)::value;
            const uint32_t stg = slot_addr(sb, S_STG) + w * 16384 + (wq * 16 + g) * 128;
            const bool odd = g & 1;
            const uint32_t o0 = (((odd ? 4 : 0) + c) ^ g) << 4, o1 = (((odd ? 0 : 4) + c) ^ g) << 4;
#pragma unroll
            for (int u = 0; u < 2; u++)
#pragma unroll
                for (int i = 0; i < 2; i++) {
                    const uint32_t* e = pk + 16 * (2 * R + u) + 4 * i;
                    asm volatile("st.shared.v4.u32 [%0], {%1, %2, %3, %4};" :: "r"(stg + u * 8192 + i * 1024 + o0),
                                 "r"(odd ? e[8] : e[0]), "r"(odd ? e[9] : e[1]), "r"(odd ? e[10] : e[2]), "r"(odd ? e[11] : e[3]) : "memory");
                    asm volatile("st.shared.v4.u32 [%0], {%1, %2, %3, %4};" :: "r"(stg + u * 8192 + i * 1024 + o1),
                                 "r"(odd ? e[0] : e[8]), "r"(odd ? e[1] : e[9]), "r"(odd ? e[2] : e[10]), "r"(odd ? e[3] : e[11]) : "memory");
                }
            asm volatile("fence.proxy.async.shared::cta;" ::: "memory");
            __syncwarp();
            if (lane == 0) mbar_arrive(bar_addr(sb, B_STG + R));
        };
        {
            float acc[128];
            uint32_t p[16];
            const uint64_t dp = desc_sw128(sb + SM_P0 + w * 8192, 16);
            mbar_wait(bar_addr(sb, B_PROJ), 0);
            uint32_t pf[4 * kG1Rs];
            {
                const int row = w * 64 + wq * 16 + (lane & 7) + ((lane >> 3) & 1) * 8;
#pragma unroll
                for (int k = 0; k < kG1Rs; k++) {
                    const int chunk = 2 * k + (lane >> 4);
                    asm volatile("ldmatrix.sync.aligned.m8n8.x4.shared.b16 {%0, %1, %2, %3}, [%4];"
                                 : "=r"(pf[4 * k]), "=r"(pf[4 * k + 1]), "=r"(pf[4 * k + 2]), "=r"(pf[4 * k + 3])
                                 : "r"(sb + SM_P0 + (k >> 2) * 16384 + row * 128 + (((chunk & 7) ^ (row & 7)) << 4)));
                }
            }
            int ks = 0, kph = 0;
#pragma unroll 1
            for (int t = 0; t < 8; t++) {
                float s[32];
                const int vs = ks == 0 ? 4 : ks - 1, vph = ks == 0 ? kph ^ 1 : kph;
                if (w == 1) bar_sync<2>(); else if (t > 0) bar_sync<3>();
                if (t > 0) {
                    mbar_wait(bar_addr(sb, B_FULL + vs), vph);
                    const uint64_t dv = desc_sw128(slot_addr(sb, vs), 8192);
                    wg_fence();
#pragma unroll
                    for (int k = 0; k < 4; k++)
                        wgmma_n256_rs_tb(acc, p[4 * k], p[4 * k + 1], p[4 * k + 2], p[4 * k + 3], dv + ((k * 2048) >> 4), (t - 1 + k) > 0);
                    wg_commit();
                }
                mbar_wait(bar_addr(sb, B_FULL + ks), kph);
                const uint64_t dk = desc_sw128(slot_addr(sb, ks), 16);
                wg_fence();
#pragma unroll
                for (int k = 0; k < 16; k++) {
                    if (k < kG1Rs)
                        wgmma_n64_rs(s, pf[4 * k], pf[4 * k + 1], pf[4 * k + 2], pf[4 * k + 3], dk + (((k >> 2) * 8192 + (k & 3) * 32) >> 4), k > 0);
                    else
                        wgmma_n64_ss(s, dp + (((k >> 2) * 16384 + (k & 3) * 32) >> 4), dk + (((k >> 2) * 8192 + (k & 3) * 32) >> 4), k > 0);
                }
                wg_commit();
                if (w == 0) bar_arrive<2>(); else bar_arrive<3>();
                if (t > 0) {
                    wg_wait<1>();
                    if (lane == 0) release_pair(bar_addr(sb, B_EMPTY + vs), rank, wq == 0 ? 2 : 1);
                }
                wg_wait<0>();
                fence_regs(s);
                if (lane == 0) release_pair(bar_addr(sb, B_EMPTY + ks), rank);
                mbar_wait(bar_addr(sb, B_NORM + (t & 3)), (t >> 2) & 1);
                const uint32_t nb = sb + SM_NORM + (t & 3) * 256 + c * 8;
                float bias[16];
#pragma unroll
                for (int j = 0; j < 8; j++)
                    asm volatile("ld.shared.v2.f32 {%0, %1}, [%2];" : "=f"(bias[2 * j]), "=f"(bias[2 * j + 1]) : "r"(nb + j * 32) : "memory");
#pragma unroll
                for (int j = 0; j < 8; j++) {
                    const float bx = bias[2 * j], by = bias[2 * j + 1];
                    const float p00 = ex2(fmaf(s[4 * j], kC1, bx)), p01 = ex2(fmaf(s[4 * j + 1], kC1, by));
                    const float p10 = ex2(fmaf(s[4 * j + 2], kC1, bx)), p11 = ex2(fmaf(s[4 * j + 3], kC1, by));
                    ks0 += p00 + p01;
                    ks1 += p10 + p11;
                    p[2 * j] = pack_bf16(p00, p01);
                    p[2 * j + 1] = pack_bf16(p10, p11);
                }
                ks += 2;
                if (ks >= 5) { ks -= 5; kph ^= 1; }
            }
            if (w == 1) bar_sync<2>(); else bar_sync<3>();
            mbar_wait(bar_addr(sb, B_FULL + 0), 1);
            {
                const uint64_t dv = desc_sw128(slot_addr(sb, 0), 8192);
                wg_fence();
#pragma unroll
                for (int k = 0; k < 4; k++)
                    wgmma_n256_rs_tb(acc, p[4 * k], p[4 * k + 1], p[4 * k + 2], p[4 * k + 3], dv + ((k * 2048) >> 4), 1);
                wg_commit();
            }
            if (w == 0) bar_arrive<2>();
            wg_wait<0>();
            fence_regs(acc);
            ks0 += __shfl_xor_sync(0xffffffffu, ks0, 1); ks0 += __shfl_xor_sync(0xffffffffu, ks0, 2);
            ks1 += __shfl_xor_sync(0xffffffffu, ks1, 1); ks1 += __shfl_xor_sync(0xffffffffu, ks1, 2);
            if (c == 0) {
                asm volatile("st.shared.f32 [%0], %1;" :: "r"(sb + SM_KS + (w * 64 + wq * 16 + g) * 4), "f"(ks0) : "memory");
                asm volatile("st.shared.f32 [%0], %1;" :: "r"(sb + SM_KS + (w * 64 + wq * 16 + g + 8) * 4), "f"(ks1) : "memory");
            }
#pragma unroll
            for (int t = 0; t < 8; t++)
#pragma unroll
                for (int i = 0; i < 2; i++)
#pragma unroll
                    for (int jj = 0; jj < 4; jj++)
                        pk[8 * t + 4 * i + jj] = pack_bf16(acc[16 * t + 4 * jj + 2 * i], acc[16 * t + 4 * jj + 2 * i + 1]);
            auto load_a = [&]() {
                mbar_wait(bar_addr(sb, B_FULL + (w == 0 ? S_QA : S_QB)), 1);
                load_q_frags(f, qb0, qb1, slot_addr(sb, w == 0 ? S_QA : S_QB), wq, lane);
                asm volatile("fence.proxy.async.shared::cta;" ::: "memory");
                __syncwarp();
                if (lane == 0) mbar_arrive(bar_addr(sb, B_ACONS + w));
            };
            bar_sync<3>();
            stage(Int<0>{});
            load_a();
        }

        uint32_t phi[64], phib[64];
        const uint32_t qsb = slot_addr(sb, w == 0 ? S_QA : S_QB);
        {
            const uint32_t p0 = sb + SM_P0, po01 = slot_addr(sb, S_PO01), po23 = slot_addr(sb, S_PO23);
            float a[64];
            gemm3(a, f, p0, p0 + 32768);
            wg_wait<0>();
            fence_regs(a);
            exp_to_regs<0>(phi, a, qb0, qb1);
            if (w == 1) {
                mbar_wait(bar_addr(sb, B_SFREE + 0), 0);
                stage(Int<1>{});
            }
            mbar_wait(bar_addr(sb, B_PO01), 0);
            mbar_wait(bar_addr(sb, B_PO23), 0);
            gemm3(a, f, po01, po23);
            if (w == 0) {
                mbar_wait(bar_addr(sb, B_SFREE + 0), 0);
                stage(Int<1>{});
            }
            wg_wait<0>();
            fence_regs(a);
            exp_to_regs<32>(phi, a, qb0, qb1);
            mbar_wait(bar_addr(sb, B_FULL + (w == 0 ? S_QA : S_QB)), 0);
            float s0 = 0.f, s1 = 0.f;
            wg_fence();
            gemm3_ss<0>(a, qsb, p0);
            tile_sumsq<0>(s0, s1, qsb, wq, lane);
            gemm3_ss<8>(a, qsb, p0 + 32768);
            wg_commit();
            tile_sumsq<8>(s0, s1, qsb, wq, lane);
            s0 += __shfl_xor_sync(0xffffffffu, s0, 1); s1 += __shfl_xor_sync(0xffffffffu, s1, 1);
            s0 += __shfl_xor_sync(0xffffffffu, s0, 2); s1 += __shfl_xor_sync(0xffffffffu, s1, 2);
            qb0 = fmaf(s0, kC2, kC3);
            qb1 = fmaf(s1, kC2, kC3);
            wg_wait<0>();
            fence_regs(a);
            pin_after(qb0, qb1, mbar_arrive_lane0(bar_addr(sb, B_P0DEAD), lane), rank >> 8);
            exp_to_regs<0>(phib, a, qb0, qb1);
            wg_fence();
            gemm3_ss<0>(a, qsb, po01);
            gemm3_ss<8>(a, qsb, po23);
            wg_commit();
            wg_wait<0>();
            fence_regs(a);
            if (w == 0 && lane == 0) mbar_arrive(bar_addr(sb, B_B0DEAD));
            pin_after(qb0, qb1, mbar_arrive_lane0(bar_addr(sb, B_PDEAD), lane), rank >> 8);
            exp_to_regs<32>(phib, a, qb0, qb1);
        }
        asm volatile("barrier.cluster.arrive.relaxed.aligned;" ::: "memory");
        {
            const uint32_t kvb[4] = {sb + SM_P0, sb + SM_P0 + 32768, slot_addr(sb, S_STG), slot_addr(sb, S_PO01)};
            const uint32_t mo = rank * 128 * 128, mx = (rank ^ 1) * 128 * 128;
            const int orow = h * kSeq + sc * 512 + rank * 256 + w * 64 + wq * 16 + g;
            __nv_bfloat16* pA = out + (size_t)orow * kDim + c * 8;
            __nv_bfloat16* pB = pA + 128 * kDim;
            float iA0, iA1, iB0, iB1;
            auto take_turn = [&](bool first) { if (w == 1) bar_sync<2>(); else if (!first) bar_sync<3>(); };
            auto give_turn = [&](bool last) { if (w == 0) bar_arrive<2>(); else if (!last) bar_arrive<3>(); };
            {
                float e[36];
                const uint32_t lbo = slot_addr(sb, S_QA) - kvb[0];
                auto tile0 = [&](const uint32_t (&ph)[64], bool first) {
                    const uint64_t d0 = desc_sw128(kvb[0] + mo, lbo), d1 = desc_sw128(kvb[0] + mx, lbo);
                    take_turn(first);
                    wg_fence();
#pragma unroll
                    for (int k = 0; k < 16; k++)
                        wgmma_n72_rs_tb(e, ph[4 * k], ph[4 * k + 1], ph[4 * k + 2], ph[4 * k + 3], (k < 8 ? d0 : d1) + (((k & 7) * 2048) >> 4), k > 0);
                    wg_commit();
                    give_turn(false);
                    wg_wait<0>();
                    fence_regs(e);
                };
                mbar_wait(bar_addr(sb, B_KV + 0), 0);
                mbar_wait(bar_addr(sb, B_KSUM), 0);
                tile0(phi, true);
                iA0 = __fdividef(1.f, e[32] + 1e-6f);
                iA1 = __fdividef(1.f, e[34] + 1e-6f);
                store_out(e, iA0, iA1, pA);
                tile0(phib, false);
                iB0 = __fdividef(1.f, e[32] + 1e-6f);
                iB1 = __fdividef(1.f, e[34] + 1e-6f);
                store_out(e, iB0, iB1, pB);
            }
#pragma unroll
            for (int i = 2; i < 8; i++) {
                const int b = i >> 1;
                float o[32];
                const uint64_t d0 = desc_sw128(kvb[b] + mo, 16), d1 = desc_sw128(kvb[b] + mx, 16);
                if (!(i & 1)) mbar_wait(bar_addr(sb, B_KV + b), 0);
                take_turn(false);
                wg_fence();
#pragma unroll
                for (int k = 0; k < 16; k++) {
                    const uint32_t (&ph)[64] = (i & 1) ? phib : phi;
                    wgmma_n64_rs_tb(o, ph[4 * k], ph[4 * k + 1], ph[4 * k + 2], ph[4 * k + 3], (k < 8 ? d0 : d1) + (((k & 7) * 2048) >> 4), k > 0);
                }
                wg_commit();
                give_turn(i == 7);
                wg_wait<0>();
                fence_regs(o);
                if (i & 1) store_out(o, iB0, iB1, pB + b * 64); else store_out(o, iA0, iA1, pA + b * 64);
            }
        }
        asm volatile("barrier.cluster.wait.aligned;" ::: "memory");
    }
}

typedef CUresult (*EncodeTiledFn)(CUtensorMap*, CUtensorMapDataType, cuuint32_t, void*, const cuuint64_t*, const cuuint64_t*,
                                  const cuuint32_t*, const cuuint32_t*, CUtensorMapInterleave, CUtensorMapSwizzle,
                                  CUtensorMapL2promotion, CUtensorMapFloatOOBfill);

bool make_map(EncodeTiledFn enc, CUtensorMap* m, const void* base, uint64_t rows, uint32_t box_rows) {
    cuuint64_t dims[3] = {64, rows, 4};
    cuuint64_t strides[2] = {512, 128};
    cuuint32_t box[3] = {64, box_rows, 2};
    cuuint32_t es[3] = {1, 1, 1};
    return enc(m, CU_TENSOR_MAP_DATA_TYPE_BFLOAT16, 3, const_cast<void*>(base), dims, strides, box, es,
               CU_TENSOR_MAP_INTERLEAVE_NONE, CU_TENSOR_MAP_SWIZZLE_128B, CU_TENSOR_MAP_L2_PROMOTION_L2_128B,
               CU_TENSOR_MAP_FLOAT_OOB_FILL_NONE) == CUDA_SUCCESS;
}

}

extern "C" void kernel_launch(void* const* d_in, const int* in_sizes, int n_in, void* d_out, int out_size) {
    (void)in_sizes; (void)n_in; (void)out_size;
    static EncodeTiledFn enc = nullptr;
    if (!enc) {
        void* fn = nullptr;
        cudaDriverEntryPointQueryResult qr;
        if (cudaGetDriverEntryPoint("cuTensorMapEncodeTiled", &fn, cudaEnableDefault, &qr) != cudaSuccess || !fn) return;
        enc = (EncodeTiledFn)fn;
        cudaFuncSetAttribute(performer_kernel, cudaFuncAttributeMaxDynamicSharedMemorySize, SM_TOTAL);
    }
    CUtensorMap tq, tk, tv, tp;
    if (!make_map(enc, &tq, d_in[0], kHeads * kSeq, 64) || !make_map(enc, &tk, d_in[1], kHeads * kSeq, 64) ||
        !make_map(enc, &tv, d_in[2], kHeads * kSeq, 64) || !make_map(enc, &tp, d_in[3], 256, 128)) return;
    performer_kernel<<<128, 384, SM_TOTAL, cudaStreamPerThread>>>(tq, tk, tv, tp, (const uint8_t*)d_in[1], (const uint8_t*)d_in[3],
                                                                    (__nv_bfloat16*)d_out);
}
```
